```python
import torch

def _softmax(x, axis=-1):
    return torch.softmax(x, dim=axis)
def _gelu(x):
    return torch.nn.functional.gelu(x, approximate="tanh")
def _silu(x):
    return torch.nn.functional.silu(x)
def _sigmoid(x):
    return torch.sigmoid(x)
def _layernorm(x, axis=-1, eps=1e-5):
    m = x.mean(dim=axis, keepdim=True)
    v = x.var(dim=axis, keepdim=True, unbiased=False)
    return (x - m) / torch.sqrt(v + eps)
def _scatter_add(tgt, idx, src, axis=0):
    return tgt.clone().index_add_(axis, idx, src)
def _segment_sum(src, seg, n):
    out = torch.zeros((n,) + src.shape[1:], dtype=src.dtype)
    return out.index_add_(0, seg, src)
def _pad(x, pw):
    flat = tuple(v for pair in reversed(pw) for v in pair)
    return torch.nn.functional.pad(x, flat)

kernel_name = 'interleave_layers__grouped_kv_mqa__dense_activation_silu__prompt'

def setup_inputs():

    _w = (lambda a: (lambda t: t.to(torch.bfloat16) if t.is_floating_point() else t)(torch.as_tensor(a)))
    def _A_setup():
        B, S, D, H = 1, 2048, 512, 32
        Dh = D // H
        return {
            "x": _w((lambda *s: torch.randn(*s, dtype=torch.bfloat16) * 0.05)(B, S, D)),
            "wq": _w((lambda *s: torch.randn(*s, dtype=torch.bfloat16) * 0.05)(D, H * Dh)),
            "wk": _w((lambda *s: torch.randn(*s, dtype=torch.bfloat16) * 0.05)(D, Dh)),
            "wv": _w((lambda *s: torch.randn(*s, dtype=torch.bfloat16) * 0.05)(D, Dh)),
            "wo": _w((lambda *s: torch.randn(*s, dtype=torch.bfloat16) * 0.05)(H * Dh, D)),
        }
    _A_in = _A_setup()

    def _B_setup():
        B, S, D, F = 1, 2048, 512, 1792
        return {
            "x": _w((lambda *s: torch.randn(*s, dtype=torch.bfloat16) * 0.05)(B, S, D)),
            "w1": _w((lambda *s: torch.randn(*s, dtype=torch.bfloat16) * 0.8)(D, F) * (D ** -0.5)),
            "w2": _w((lambda *s: torch.randn(*s, dtype=torch.bfloat16) * 0.8)(F, D) * (F ** -0.5)),
        }
    _B_in = _B_setup()

    return {
        "A_x": _A_in["x"],
        "A_wq": _A_in["wq"],
        "A_wk": _A_in["wk"],
        "A_wv": _A_in["wv"],
        "A_wo": _A_in["wo"],
        "B_x": _B_in["x"],
        "B_w1": _B_in["w1"],
        "B_w2": _B_in["w2"],
    }

def reference(A_x, A_wq, A_wk, A_wv, A_wo, B_x, B_w1, B_w2):
    def _A_ref(x, wq, wk, wv, wo):
        B, S, D = x.shape
        H = 32
        Dh = D // H
        q = (lambda x, *d: x.permute(*d))((x @ wq).reshape(B, S, H, Dh), 0, 2, 1, 3)
        k = x @ wk
        v = x @ wv
        scores = torch.einsum("bhqd,bkd->bhqk", q, k) * (Dh ** -0.5)
        p = _softmax(scores, axis=-1)
        o = torch.einsum("bhqk,bkd->bhqd", p, v)
        return (lambda x, *d: x.permute(*d))(o, 0, 2, 1, 3).reshape(B, S, H * Dh) @ wo

    def _B_ref(x, w1, w2):
        h = torch.einsum("bsd,df->bsf", x, w1)
        h = _silu(h)
        out = torch.einsum("bsf,fd->bsd", h, w2)
        return out

    x = A_x
    x = x + _A_ref(_layernorm(x, axis=-1), A_wq, A_wk, A_wv, A_wo)
    x = x + _B_ref(_layernorm(x, axis=-1), B_w1, B_w2)
    x = x + _A_ref(_layernorm(x, axis=-1), A_wq, A_wk, A_wv, A_wo)
    x = x + _B_ref(_layernorm(x, axis=-1), B_w1, B_w2)
    return x
```

```cpp
#include <cuda_runtime.h>
#include <cuda_bf16.h>
#include <cuda.h>
#include <stdint.h>

namespace {

typedef __nv_bfloat16 bf16;
constexpr int S_ = 2048, D_ = 512, F_ = 1792;
constexpr float LN_EPS = 1e-5f;
constexpr float QSCALE = 0.25f * 1.4426950408889634f;

constexpr uint32_t LUT_MASK_EVEN = 0x55, LUT_MASK_ODD = 0x5D;
constexpr float SAFE_SCORE_BOUND = 80.0f;

__device__ __align__(1024) bf16 g_Q[S_ * D_];
__device__ __align__(1024) uint8_t g_K[S_ * 32];
__device__ __align__(1024) uint8_t g_V[S_ * 32];
__device__ __align__(1024) float g_kmax[32 * 16];
__device__ __align__(1024) bf16 g_O[S_ * D_];
__device__ __align__(1024) bf16 g_x1[S_ * D_];
__device__ __align__(1024) bf16 g_x2[S_ * D_];
__device__ __align__(1024) bf16 g_h[S_ * F_];
__device__ __align__(1024) float2 g_statA[S_ * 8];
__device__ __align__(1024) float2 g_statB[S_ * 8];
__device__ __align__(1024) float g_csQKV[544];
__device__ __align__(1024) float g_cs1[F_];

__device__ __forceinline__ uint32_t smem_u32(const void* p) { return (uint32_t)__cvta_generic_to_shared(p); }
__device__ __forceinline__ void mbar_init(uint32_t b, uint32_t c) { asm volatile("mbarrier.init.shared::cta.b64 [%0], %1;" ::"r"(b), "r"(c)); }
__device__ __forceinline__ void mbar_fence_init() { asm volatile("fence.mbarrier_init.release.cluster;" ::: "memory"); }
__device__ __forceinline__ void mbar_expect(uint32_t b, uint32_t bytes) {
  asm volatile("mbarrier.arrive.expect_tx.shared::cta.b64 _, [%0], %1;" ::"r"(b), "r"(bytes) : "memory");
}
__device__ __forceinline__ void mbar_arrive(uint32_t b) { asm volatile("mbarrier.arrive.shared::cta.b64 _, [%0];" ::"r"(b) : "memory"); }
__device__ __forceinline__ void mbar_wait(uint32_t b, uint32_t ph) {
  asm volatile(
      "{.reg .pred p;\n"
      "LAB_WAIT:\n"
      "mbarrier.try_wait.parity.shared::cta.b64 p, [%0], %1;\n"
      "@p bra LAB_DONE;\n"
      "bra LAB_WAIT;\n"
      "LAB_DONE:\n}" ::"r"(b), "r"(ph) : "memory");
}
__device__ __forceinline__ void bulk_g2s(uint32_t dst, const void* src, uint32_t bytes, uint32_t bar) {
  asm volatile("cp.async.bulk.shared::cluster.global.mbarrier::complete_tx::bytes [%0], [%1], %2, [%3];" ::"r"(dst), "l"(src), "r"(bytes), "r"(bar) : "memory");
}
__device__ __forceinline__ void tma2d(uint32_t dst, const CUtensorMap* m, int c0, int c1, uint32_t bar) {
  asm volatile("cp.async.bulk.tensor.2d.shared::cluster.global.mbarrier::complete_tx::bytes [%0], [%1, {%3, %4}], [%2];"
               ::"r"(dst), "l"(m), "r"(bar), "r"(c0), "r"(c1) : "memory");
}
__device__ __forceinline__ void tma3d(uint32_t dst, const CUtensorMap* m, int c0, int c1, int c2, uint32_t bar) {
  asm volatile("cp.async.bulk.tensor.3d.shared::cluster.global.mbarrier::complete_tx::bytes [%0], [%1, {%3, %4, %5}], [%2];"
               ::"r"(dst), "l"(m), "r"(bar), "r"(c0), "r"(c1), "r"(c2) : "memory");
}
__device__ __forceinline__ void tma2d_store(const CUtensorMap* m, int c0, int c1, uint32_t src) {
  asm volatile("cp.async.bulk.tensor.2d.global.shared::cta.bulk_group [%0, {%2, %3}], [%1];" ::"l"(m), "r"(src), "r"(c0), "r"(c1) : "memory");
}
__device__ __forceinline__ void tma3d_store(const CUtensorMap* m, int c0, int c1, int c2, uint32_t src) {
  asm volatile("cp.async.bulk.tensor.3d.global.shared::cta.bulk_group [%0, {%2, %3, %4}], [%1];" ::"l"(m), "r"(src), "r"(c0), "r"(c1), "r"(c2) : "memory");
}
__device__ __forceinline__ void bulk_commit_wait_all() {
  asm volatile("cp.async.bulk.commit_group;" ::: "memory");
  asm volatile("cp.async.bulk.wait_group 0;" ::: "memory");
}
__device__ __forceinline__ void fence_async_smem() { asm volatile("fence.proxy.async.shared::cta;" ::: "memory"); }
__device__ __forceinline__ void pdl_trigger() { asm volatile("griddepcontrol.launch_dependents;" ::: "memory"); }
__device__ __forceinline__ void pdl_wait() { asm volatile("griddepcontrol.wait;" ::: "memory"); }
__device__ __forceinline__ void bar_sync(int id, int n) { asm volatile("bar.sync %0, %1;" ::"r"(id), "r"(n) : "memory"); }
__device__ __forceinline__ void wg_fence() { asm volatile("wgmma.fence.sync.aligned;" ::: "memory"); }
__device__ __forceinline__ void wg_commit() { asm volatile("wgmma.commit_group.sync.aligned;" ::: "memory"); }
template <int N> __device__ __forceinline__ void wg_wait() { asm volatile("wgmma.wait_group.sync.aligned %0;" ::"n"(N) : "memory"); }
__device__ __forceinline__ uint64_t mkdesc(uint32_t addr, uint32_t lbo, uint32_t sbo, uint32_t swz) {
  return (uint64_t)((addr & 0x3FFFF) >> 4) | ((uint64_t)(lbo >> 4) << 16) | ((uint64_t)(sbo >> 4) << 32) | ((uint64_t)swz << 62);
}
template <int N> __device__ __forceinline__ void fence_regs(float* d) {
#pragma unroll
  for (int i = 0; i < N; i++) asm volatile("" : "+f"(d[i])::"memory");
}
template <int N> __device__ __forceinline__ void fence_regs_u(uint32_t* d) {
#pragma unroll
  for (int i = 0; i < N; i++) asm volatile("" : "+r"(d[i])::"memory");
}
__device__ __forceinline__ uint32_t pack_bf16(float lo, float hi) {
  uint32_t r;
  asm("cvt.rn.bf16x2.f32 %0, %1, %2;" : "=r"(r) : "f"(hi), "f"(lo));
  return r;
}
__device__ __forceinline__ float bf_lo(uint32_t u) { return __uint_as_float(u << 16); }
__device__ __forceinline__ float bf_hi(uint32_t u) { return __uint_as_float(u & 0xFFFF0000u); }
__device__ __forceinline__ float ex2f(float x) {
  float y;
  asm("ex2.approx.ftz.f32 %0, %1;" : "=f"(y) : "f"(x));
  return y;
}
__device__ __forceinline__ void stsm4(uint32_t a, uint32_t r0, uint32_t r1, uint32_t r2, uint32_t r3) {
  asm volatile("stmatrix.sync.aligned.m8n8.x4.shared.b16 [%0], {%1,%2,%3,%4};" ::"r"(a), "r"(r0), "r"(r1), "r"(r2), "r"(r3) : "memory");
}
__device__ __forceinline__ void ldsm4(uint32_t* r, uint32_t a) {
  asm volatile("ldmatrix.sync.aligned.m8n8.x4.shared.b16 {%0,%1,%2,%3}, [%4];" : "=r"(r[0]), "=r"(r[1]), "=r"(r[2]), "=r"(r[3]) : "r"(a) : "memory");
}
__device__ __forceinline__ void ldsm4t(uint32_t* r, uint32_t a) {
  asm volatile("ldmatrix.sync.aligned.m8n8.x4.trans.shared.b16 {%0,%1,%2,%3}, [%4];" : "=r"(r[0]), "=r"(r[1]), "=r"(r[2]), "=r"(r[3]) : "r"(a) : "memory");
}
__device__ __forceinline__ void mma16816(float* d, const uint32_t* a, uint32_t b0, uint32_t b1) {
  asm volatile("mma.sync.aligned.m16n8k16.row.col.f32.bf16.bf16.f32 {%0,%1,%2,%3}, {%4,%5,%6,%7}, {%8,%9}, {%0,%1,%2,%3};"
               : "+f"(d[0]), "+f"(d[1]), "+f"(d[2]), "+f"(d[3]) : "r"(a[0]), "r"(a[1]), "r"(a[2]), "r"(a[3]), "r"(b0), "r"(b1));
}
__device__ __forceinline__ void row_stats(const float2* __restrict__ st, int row, float& mean, float& rstd) {
  const float4* p = reinterpret_cast<const float4*>(st + row * 8);
  float s = 0.f, q = 0.f;
#pragma unroll
  for (int i = 0; i < 4; i++) {
    float4 v = __ldcg(p + i);
    s += v.x + v.z;
    q += v.y + v.w;
  }
  mean = s * (1.f / D_);
  float var = fmaxf(q * (1.f / D_) - mean * mean, 0.f);
  rstd = rsqrtf(var + LN_EPS);
}

__device__ __forceinline__ void wgmma_rs_n64(float* d, uint32_t a0, uint32_t a1, uint32_t a2, uint32_t a3, uint64_t descB, int scaleD){
  asm volatile("{.reg .pred p; setp.ne.b32 p, %37, 0; wgmma.mma_async.sync.aligned.m64n64k16.f32.bf16.bf16 {%0,%1,%2,%3,%4,%5,%6,%7,%8,%9,%10,%11,%12,%13,%14,%15,%16,%17,%18,%19,%20,%21,%22,%23,%24,%25,%26,%27,%28,%29,%30,%31}, {%32,%33,%34,%35}, %36, p, 1, 1, 0;}"
   : "+f"(d[0]),"+f"(d[1]),"+f"(d[2]),"+f"(d[3]),"+f"(d[4]),"+f"(d[5]),"+f"(d[6]),"+f"(d[7]),"+f"(d[8]),"+f"(d[9]),"+f"(d[10]),"+f"(d[11]),"+f"(d[12]),"+f"(d[13]),"+f"(d[14]),"+f"(d[15]),"+f"(d[16]),"+f"(d[17]),"+f"(d[18]),"+f"(d[19]),"+f"(d[20]),"+f"(d[21]),"+f"(d[22]),"+f"(d[23]),"+f"(d[24]),"+f"(d[25]),"+f"(d[26]),"+f"(d[27]),"+f"(d[28]),"+f"(d[29]),"+f"(d[30]),"+f"(d[31])
   : "r"(a0),"r"(a1),"r"(a2),"r"(a3),"l"(descB),"r"(scaleD));
}

__device__ __forceinline__ void wgmma_rs_tb_n24(float* d, uint32_t a0, uint32_t a1, uint32_t a2, uint32_t a3, uint64_t descB, int scaleD){
  asm volatile("{.reg .pred p; setp.ne.b32 p, %17, 0; wgmma.mma_async.sync.aligned.m64n24k16.f32.bf16.bf16 {%0,%1,%2,%3,%4,%5,%6,%7,%8,%9,%10,%11}, {%12,%13,%14,%15}, %16, p, 1, 1, 1;}"
   : "+f"(d[0]),"+f"(d[1]),"+f"(d[2]),"+f"(d[3]),"+f"(d[4]),"+f"(d[5]),"+f"(d[6]),"+f"(d[7]),"+f"(d[8]),"+f"(d[9]),"+f"(d[10]),"+f"(d[11])
   : "r"(a0),"r"(a1),"r"(a2),"r"(a3),"l"(descB),"r"(scaleD));
}

__device__ __forceinline__ void wgmma_ss_tb_n128(float* d, uint64_t descA, uint64_t descB, int scaleD){
  asm volatile("{.reg .pred p; setp.ne.b32 p, %66, 0; wgmma.mma_async.sync.aligned.m64n128k16.f32.bf16.bf16 {%0,%1,%2,%3,%4,%5,%6,%7,%8,%9,%10,%11,%12,%13,%14,%15,%16,%17,%18,%19,%20,%21,%22,%23,%24,%25,%26,%27,%28,%29,%30,%31,%32,%33,%34,%35,%36,%37,%38,%39,%40,%41,%42,%43,%44,%45,%46,%47,%48,%49,%50,%51,%52,%53,%54,%55,%56,%57,%58,%59,%60,%61,%62,%63}, %64, %65, p, 1, 1, 0, 1;}"
   : "+f"(d[0]),"+f"(d[1]),"+f"(d[2]),"+f"(d[3]),"+f"(d[4]),"+f"(d[5]),"+f"(d[6]),"+f"(d[7]),"+f"(d[8]),"+f"(d[9]),"+f"(d[10]),"+f"(d[11]),"+f"(d[12]),"+f"(d[13]),"+f"(d[14]),"+f"(d[15]),"+f"(d[16]),"+f"(d[17]),"+f"(d[18]),"+f"(d[19]),"+f"(d[20]),"+f"(d[21]),"+f"(d[22]),"+f"(d[23]),"+f"(d[24]),"+f"(d[25]),"+f"(d[26]),"+f"(d[27]),"+f"(d[28]),"+f"(d[29]),"+f"(d[30]),"+f"(d[31]),"+f"(d[32]),"+f"(d[33]),"+f"(d[34]),"+f"(d[35]),"+f"(d[36]),"+f"(d[37]),"+f"(d[38]),"+f"(d[39]),"+f"(d[40]),"+f"(d[41]),"+f"(d[42]),"+f"(d[43]),"+f"(d[44]),"+f"(d[45]),"+f"(d[46]),"+f"(d[47]),"+f"(d[48]),"+f"(d[49]),"+f"(d[50]),"+f"(d[51]),"+f"(d[52]),"+f"(d[53]),"+f"(d[54]),"+f"(d[55]),"+f"(d[56]),"+f"(d[57]),"+f"(d[58]),"+f"(d[59]),"+f"(d[60]),"+f"(d[61]),"+f"(d[62]),"+f"(d[63])
   : "l"(descA),"l"(descB),"r"(scaleD));
}

__device__ __forceinline__ void wgmma_ss_tb_n136(float* d, uint64_t descA, uint64_t descB, int scaleD){
  asm volatile("{.reg .pred p; setp.ne.b32 p, %70, 0; wgmma.mma_async.sync.aligned.m64n136k16.f32.bf16.bf16 {%0,%1,%2,%3,%4,%5,%6,%7,%8,%9,%10,%11,%12,%13,%14,%15,%16,%17,%18,%19,%20,%21,%22,%23,%24,%25,%26,%27,%28,%29,%30,%31,%32,%33,%34,%35,%36,%37,%38,%39,%40,%41,%42,%43,%44,%45,%46,%47,%48,%49,%50,%51,%52,%53,%54,%55,%56,%57,%58,%59,%60,%61,%62,%63,%64,%65,%66,%67}, %68, %69, p, 1, 1, 0, 1;}"
   : "+f"(d[0]),"+f"(d[1]),"+f"(d[2]),"+f"(d[3]),"+f"(d[4]),"+f"(d[5]),"+f"(d[6]),"+f"(d[7]),"+f"(d[8]),"+f"(d[9]),"+f"(d[10]),"+f"(d[11]),"+f"(d[12]),"+f"(d[13]),"+f"(d[14]),"+f"(d[15]),"+f"(d[16]),"+f"(d[17]),"+f"(d[18]),"+f"(d[19]),"+f"(d[20]),"+f"(d[21]),"+f"(d[22]),"+f"(d[23]),"+f"(d[24]),"+f"(d[25]),"+f"(d[26]),"+f"(d[27]),"+f"(d[28]),"+f"(d[29]),"+f"(d[30]),"+f"(d[31]),"+f"(d[32]),"+f"(d[33]),"+f"(d[34]),"+f"(d[35]),"+f"(d[36]),"+f"(d[37]),"+f"(d[38]),"+f"(d[39]),"+f"(d[40]),"+f"(d[41]),"+f"(d[42]),"+f"(d[43]),"+f"(d[44]),"+f"(d[45]),"+f"(d[46]),"+f"(d[47]),"+f"(d[48]),"+f"(d[49]),"+f"(d[50]),"+f"(d[51]),"+f"(d[52]),"+f"(d[53]),"+f"(d[54]),"+f"(d[55]),"+f"(d[56]),"+f"(d[57]),"+f"(d[58]),"+f"(d[59]),"+f"(d[60]),"+f"(d[61]),"+f"(d[62]),"+f"(d[63]),"+f"(d[64]),"+f"(d[65]),"+f"(d[66]),"+f"(d[67])
   : "l"(descA),"l"(descB),"r"(scaleD));
}

__device__ __forceinline__ void wgmma_ss_tb_n224(float* d, uint64_t descA, uint64_t descB, int scaleD){
  asm volatile("{.reg .pred p; setp.ne.b32 p, %114, 0; wgmma.mma_async.sync.aligned.m64n224k16.f32.bf16.bf16 {%0,%1,%2,%3,%4,%5,%6,%7,%8,%9,%10,%11,%12,%13,%14,%15,%16,%17,%18,%19,%20,%21,%22,%23,%24,%25,%26,%27,%28,%29,%30,%31,%32,%33,%34,%35,%36,%37,%38,%39,%40,%41,%42,%43,%44,%45,%46,%47,%48,%49,%50,%51,%52,%53,%54,%55,%56,%57,%58,%59,%60,%61,%62,%63,%64,%65,%66,%67,%68,%69,%70,%71,%72,%73,%74,%75,%76,%77,%78,%79,%80,%81,%82,%83,%84,%85,%86,%87,%88,%89,%90,%91,%92,%93,%94,%95,%96,%97,%98,%99,%100,%101,%102,%103,%104,%105,%106,%107,%108,%109,%110,%111}, %112, %113, p, 1, 1, 0, 1;}"
   : "+f"(d[0]),"+f"(d[1]),"+f"(d[2]),"+f"(d[3]),"+f"(d[4]),"+f"(d[5]),"+f"(d[6]),"+f"(d[7]),"+f"(d[8]),"+f"(d[9]),"+f"(d[10]),"+f"(d[11]),"+f"(d[12]),"+f"(d[13]),"+f"(d[14]),"+f"(d[15]),"+f"(d[16]),"+f"(d[17]),"+f"(d[18]),"+f"(d[19]),"+f"(d[20]),"+f"(d[21]),"+f"(d[22]),"+f"(d[23]),"+f"(d[24]),"+f"(d[25]),"+f"(d[26]),"+f"(d[27]),"+f"(d[28]),"+f"(d[29]),"+f"(d[30]),"+f"(d[31]),"+f"(d[32]),"+f"(d[33]),"+f"(d[34]),"+f"(d[35]),"+f"(d[36]),"+f"(d[37]),"+f"(d[38]),"+f"(d[39]),"+f"(d[40]),"+f"(d[41]),"+f"(d[42]),"+f"(d[43]),"+f"(d[44]),"+f"(d[45]),"+f"(d[46]),"+f"(d[47]),"+f"(d[48]),"+f"(d[49]),"+f"(d[50]),"+f"(d[51]),"+f"(d[52]),"+f"(d[53]),"+f"(d[54]),"+f"(d[55]),"+f"(d[56]),"+f"(d[57]),"+f"(d[58]),"+f"(d[59]),"+f"(d[60]),"+f"(d[61]),"+f"(d[62]),"+f"(d[63]),"+f"(d[64]),"+f"(d[65]),"+f"(d[66]),"+f"(d[67]),"+f"(d[68]),"+f"(d[69]),"+f"(d[70]),"+f"(d[71]),"+f"(d[72]),"+f"(d[73]),"+f"(d[74]),"+f"(d[75]),"+f"(d[76]),"+f"(d[77]),"+f"(d[78]),"+f"(d[79]),"+f"(d[80]),"+f"(d[81]),"+f"(d[82]),"+f"(d[83]),"+f"(d[84]),"+f"(d[85]),"+f"(d[86]),"+f"(d[87]),"+f"(d[88]),"+f"(d[89]),"+f"(d[90]),"+f"(d[91]),"+f"(d[92]),"+f"(d[93]),"+f"(d[94]),"+f"(d[95]),"+f"(d[96]),"+f"(d[97]),"+f"(d[98]),"+f"(d[99]),"+f"(d[100]),"+f"(d[101]),"+f"(d[102]),"+f"(d[103]),"+f"(d[104]),"+f"(d[105]),"+f"(d[106]),"+f"(d[107]),"+f"(d[108]),"+f"(d[109]),"+f"(d[110]),"+f"(d[111])
   : "l"(descA),"l"(descB),"r"(scaleD));
}

__global__ void __launch_bounds__(256) prep_kernel(const bf16* __restrict__ x, const bf16* __restrict__ wq, const bf16* __restrict__ wk,
                                                    const bf16* __restrict__ wv, const bf16* __restrict__ w1, const bf16* __restrict__ wo,
                                                    const bf16* __restrict__ w2) {
  pdl_trigger();
  const int b = blockIdx.x, tid = threadIdx.x, lane = tid & 31, warp = tid >> 5;
  __shared__ float red[8][32];
  if (tid == 0) {
    constexpr uint32_t WO_B = D_ * D_ * 2, W2_B = F_ * D_ * 2, PER = (WO_B + W2_B) / 128;
    if (b < 128) {
      uint32_t off = b * PER;
      if (off < WO_B) {
        uint32_t n = min(PER, WO_B - off);
        asm volatile("cp.async.bulk.prefetch.L2.global [%0], %1;" ::"l"((const char*)wo + off), "r"(n));
        if (n < PER) asm volatile("cp.async.bulk.prefetch.L2.global [%0], %1;" ::"l"((const char*)w2), "r"(PER - n));
      } else {
        asm volatile("cp.async.bulk.prefetch.L2.global [%0], %1;" ::"l"((const char*)w2 + (off - WO_B)), "r"(PER));
      }
    }
  }
  float acc[8];
  const bool do_cs = b < 73;
  if (do_cs) {
    const int c = tid & 3, rg = tid >> 2;
    const bf16* p;
    int pitch;
    if (b < 16) { p = wq + 32 * b + 8 * c; pitch = D_; }
    else if (b < 72) { p = w1 + 32 * (b - 16) + 8 * c; pitch = F_; }
    else { p = (c < 2 ? wk : wv) + 8 * (c & 1); pitch = 16; }
    uint4 v[8];
#pragma unroll
    for (int r = 0; r < 8; r++) v[r] = __ldg(reinterpret_cast<const uint4*>(p + (size_t)(rg * 8 + r) * pitch));
#pragma unroll
    for (int i = 0; i < 8; i++) acc[i] = 0.f;
#pragma unroll
    for (int r = 0; r < 8; r++) {
      acc[0] += bf_lo(v[r].x); acc[1] += bf_hi(v[r].x); acc[2] += bf_lo(v[r].y); acc[3] += bf_hi(v[r].y);
      acc[4] += bf_lo(v[r].z); acc[5] += bf_hi(v[r].z); acc[6] += bf_lo(v[r].w); acc[7] += bf_hi(v[r].w);
    }
  }
  if (b < 128) {
#pragma unroll
    for (int rr = 0; rr < 2; rr++) {
      const int row = b * 16 + warp * 2 + rr;
      const uint4* p = reinterpret_cast<const uint4*>(x + (size_t)row * D_);
#pragma unroll
      for (int hlf = 0; hlf < 2; hlf++) {
        uint4 v = __ldg(p + hlf * 32 + lane);
        float f[8] = {bf_lo(v.x), bf_hi(v.x), bf_lo(v.y), bf_hi(v.y), bf_lo(v.z), bf_hi(v.z), bf_lo(v.w), bf_hi(v.w)};
        float s = 0.f, q = 0.f;
#pragma unroll
        for (int i = 0; i < 8; i++) { s += f[i]; q += f[i] * f[i]; }
#pragma unroll
        for (int o = 1; o < 8; o <<= 1) { s += __shfl_xor_sync(~0u, s, o); q += __shfl_xor_sync(~0u, q, o); }
        if ((lane & 7) == 0) g_statA[row * 8 + hlf * 4 + (lane >> 3)] = make_float2(s, q);
      }
    }
  }
  if (do_cs) {
#pragma unroll
    for (int i = 0; i < 8; i++) {
#pragma unroll
      for (int o = 4; o < 32; o <<= 1) acc[i] += __shfl_xor_sync(~0u, acc[i], o);
    }
    if (lane < 4) {
#pragma unroll
      for (int i = 0; i < 8; i++) red[warp][lane * 8 + i] = acc[i];
    }
    __syncthreads();
    if (tid < 32) {
      float s = 0.f;
#pragma unroll
      for (int w = 0; w < 8; w++) s += red[w][tid];
      if (b < 16) g_csQKV[32 * b + tid] = s;
      else if (b < 72) g_cs1[32 * (b - 16) + tid] = s;
      else g_csQKV[512 + tid] = s;
    }
  }
}

constexpr int QKV_STAGES = 6, QKV_STAGE_B = 32768;
constexpr int QKV_SMEM = QKV_STAGES * QKV_STAGE_B + 1024 + 256;

template <bool FIRST>
__global__ void __launch_bounds__(160, 1) qkv_kernel(const __grid_constant__ CUtensorMap mA, const __grid_constant__ CUtensorMap mWq,
                                                      const __grid_constant__ CUtensorMap mWk, const __grid_constant__ CUtensorMap mWv) {
  extern __shared__ uint8_t smraw[];
  const uint32_t sb = (smem_u32(smraw) + 1023) & ~1023u;
  const uint32_t bars = sb + QKV_STAGES * QKV_STAGE_B;
  const int tid = threadIdx.x, lane = tid & 31, warp = tid >> 5;
  const int tb = blockIdx.x >> 2, hg = blockIdx.x & 3;
  pdl_trigger();
  if (tid == 0) {
    for (int i = 0; i < QKV_STAGES; i++) { mbar_init(bars + i * 8, 1); mbar_init(bars + (QKV_STAGES + i) * 8, 4); }
    mbar_fence_init();
  }
  __syncthreads();
  if (warp == 4) {
    if (lane == 0) {
      const CUtensorMap* mKV = (hg < 2) ? &mWk : &mWv;
      const int c0 = (hg & 1) * 8;
#pragma unroll 1
      for (int kc = 0; kc < QKV_STAGES; kc++) {
        const uint32_t st = sb + kc * QKV_STAGE_B, fb = bars + kc * 8;
        mbar_expect(fb, QKV_STAGE_B);
        tma3d(st + 8192, &mWq, 0, kc * 64, hg * 2, fb);
        tma2d(st + 24576, mKV, c0, kc * 64, fb);
        if (FIRST) tma2d(st, &mA, kc * 64, tb * 64, fb);
      }
      if (!FIRST) {
        pdl_wait();
#pragma unroll 1
        for (int kc = 0; kc < QKV_STAGES; kc++) tma2d(sb + kc * QKV_STAGE_B, &mA, kc * 64, tb * 64, bars + kc * 8);
      }
#pragma unroll 1
      for (int kc = QKV_STAGES; kc < 8; kc++) {
        const int s = kc - QKV_STAGES;
        const uint32_t st = sb + s * QKV_STAGE_B, fb = bars + s * 8;
        mbar_wait(bars + (QKV_STAGES + s) * 8, 0);
        mbar_expect(fb, QKV_STAGE_B);
        tma2d(st, &mA, kc * 64, tb * 64, fb);
        tma3d(st + 8192, &mWq, 0, kc * 64, hg * 2, fb);
        tma2d(st + 24576, mKV, c0, kc * 64, fb);
      }
    }
    return;
  }
  float acc[68];
#pragma unroll
  for (int i = 0; i < 68; i++) acc[i] = 0.f;
  fence_regs<68>(acc);
#pragma unroll 1
  for (int kc = 0; kc < 8; kc++) {
    const int s = kc % QKV_STAGES;
    const uint32_t st = sb + s * QKV_STAGE_B;
    mbar_wait(bars + s * 8, kc / QKV_STAGES);
    wg_fence();
#pragma unroll
    for (int ks = 0; ks < 4; ks++)
      wgmma_ss_tb_n136(acc, mkdesc(st + ks * 32, 16, 1024, 1), mkdesc(st + 8192 + ks * 2048, 8192, 1024, 1), 1);
    wg_commit();
    if (kc < 8 - QKV_STAGES) {
      wg_wait<0>();
      if (lane == 0) mbar_arrive(bars + (QKV_STAGES + s) * 8);
    }
  }
  wg_wait<0>();
  fence_regs<68>(acc);
  pdl_wait();
  const int g = lane >> 2, t = lane & 3;
  const int r0 = tb * 64 + warp * 16 + g;
  float mean0, rstd0, mean1, rstd1;
  row_stats(g_statA, r0, mean0, rstd0);
  row_stats(g_statA, r0 + 8, mean1, rstd1);
  bar_sync(1, 128);
  const uint32_t stg = sb;
  {
    const float q0 = rstd0 * QSCALE, q1 = rstd1 * QSCALE;
    const uint32_t a0 = stg + (warp * 16 + ((lane >> 3) & 1) * 8 + (lane & 7)) * 272 + (lane >> 4) * 16;
#pragma unroll
    for (int j = 0; j < 16; j += 2) {
      const float2 ca = __ldcg(reinterpret_cast<const float2*>(g_csQKV + hg * 128 + 8 * j + 2 * t));
      const float2 cb = __ldcg(reinterpret_cast<const float2*>(g_csQKV + hg * 128 + 8 * j + 8 + 2 * t));
      const float* a = acc + 4 * j;
      stsm4(a0 + j * 16, pack_bf16((a[0] - mean0 * ca.x) * q0, (a[1] - mean0 * ca.y) * q0),
            pack_bf16((a[2] - mean1 * ca.x) * q1, (a[3] - mean1 * ca.y) * q1),
            pack_bf16((a[4] - mean0 * cb.x) * q0, (a[5] - mean0 * cb.y) * q0),
            pack_bf16((a[6] - mean1 * cb.x) * q1, (a[7] - mean1 * cb.y) * q1));
    }
  }
  {
    const float2 c = __ldcg(reinterpret_cast<const float2*>(g_csQKV + 512 + hg * 8 + 2 * t));
    uint32_t u0 = pack_bf16((acc[64] - mean0 * c.x) * rstd0, (acc[65] - mean0 * c.y) * rstd0);
    uint32_t u1 = pack_bf16((acc[66] - mean1 * c.x) * rstd1, (acc[67] - mean1 * c.y) * rstd1);
    if (hg < 2) {
      *reinterpret_cast<uint32_t*>(g_K + (r0 >> 3) * 256 + hg * 128 + (r0 & 7) * 16 + t * 4) = u0;
      *reinterpret_cast<uint32_t*>(g_K + ((r0 + 8) >> 3) * 256 + hg * 128 + (r0 & 7) * 16 + t * 4) = u1;
      float m0 = fmaxf(fabsf(bf_lo(u0)), fabsf(bf_lo(u1))), m1 = fmaxf(fabsf(bf_hi(u0)), fabsf(bf_hi(u1)));
      if (!(bf_lo(u0) == bf_lo(u0)) || !(bf_lo(u1) == bf_lo(u1))) m0 = __int_as_float(0x7f800000);
      if (!(bf_hi(u0) == bf_hi(u0)) || !(bf_hi(u1) == bf_hi(u1))) m1 = __int_as_float(0x7f800000);
#pragma unroll
      for (int o = 4; o < 32; o <<= 1) { m0 = fmaxf(m0, __shfl_xor_sync(~0u, m0, o)); m1 = fmaxf(m1, __shfl_xor_sync(~0u, m1, o)); }
      float* km = reinterpret_cast<float*>(smraw + (sb - smem_u32(smraw)) + 64 * 272);
      if (g == 0) { km[warp * 8 + 2 * t] = m0; km[warp * 8 + 2 * t + 1] = m1; }
    } else {
      const uint32_t mask = ((r0 >> 6) & 1) ? LUT_MASK_ODD : LUT_MASK_EVEN;
      if ((mask >> ((r0 >> 3) & 7)) & 1) u0 ^= 0x80008000u;
      if ((mask >> (((r0 + 8) >> 3) & 7)) & 1) u1 ^= 0x80008000u;
      *reinterpret_cast<uint32_t*>(g_V + (hg - 2) * (S_ * 16) + r0 * 16 + t * 4) = u0;
      *reinterpret_cast<uint32_t*>(g_V + (hg - 2) * (S_ * 16) + (r0 + 8) * 16 + t * 4) = u1;
    }
  }
  bar_sync(1, 128);
  if (hg < 2 && tid < 8) {
    const float* km = reinterpret_cast<const float*>(smraw + (sb - smem_u32(smraw)) + 64 * 272);
    g_kmax[tb * 16 + hg * 8 + tid] = fmaxf(fmaxf(km[tid], km[8 + tid]), fmaxf(km[16 + tid], km[24 + tid]));
  }
  const uint8_t* sp = smraw + (sb - smem_u32(smraw));
#pragma unroll
  for (int i = 0; i < 8; i++) {
    const int ch = i * 128 + tid, row = ch >> 4, c16 = ch & 15;
    const uint4 v = *reinterpret_cast<const uint4*>(sp + row * 272 + c16 * 16);
    *reinterpret_cast<uint4*>(g_Q + (size_t)(tb * 64 + row) * D_ + hg * 128 + c16 * 8) = v;
  }
}

constexpr int ATT_SMEM = 31 * 1024 + 192 * 1024 + 1024;
constexpr float LUT_MAGIC = 382.875f;

template <uint32_t MASK>
__device__ __forceinline__ void exp_pack(const float* s, uint32_t* p, uint32_t lutlane) {
#pragma unroll
  for (int i = 0; i < 16; i++) {
    if ((MASK >> (i / 2)) & 1) {
      const uint32_t b0 = __float_as_uint(s[2 * i] + LUT_MAGIC), b1 = __float_as_uint(s[2 * i + 1] + LUT_MAGIC);
      uint32_t c0, c1, w;
      asm volatile("ld.shared.u16 %0, [%1+2];" : "=r"(c0) : "r"((b0 & 0x7F80u) | lutlane));
      asm volatile("ld.shared.u32 %0, [%1];" : "=r"(c1) : "r"((b1 & 0x7F80u) | lutlane));
      asm("prmt.b32 %0, %1, %2, 0x6521;" : "=r"(w) : "r"(b0), "r"(b1));
      p[i] = w + c0 + c1;
    } else {
      p[i] = pack_bf16(ex2f(s[2 * i]), ex2f(s[2 * i + 1]));
    }
  }
}

__global__ void __launch_bounds__(512, 1) attn_kernel() {
  extern __shared__ uint8_t smraw[];
  const uint32_t sbase = smem_u32(smraw);
  const uint32_t bars = sbase;
  const uint32_t kred = sbase + 128;
  const uint32_t LUT = (sbase + 2048 + 16384 + 32767) & ~32767u;
  const uint32_t KS = LUT + 32768, VS = KS + 65536;
  uint8_t* sm0 = smraw - sbase;
  const int tid = threadIdx.x, lane = tid & 31, wg = tid >> 7, warp = (tid >> 5) & 3;
  pdl_trigger();
  if (tid == 0) {
    for (int i = 0; i < 8; i++) mbar_init(bars + i * 8, 1);
    mbar_fence_init();
  }
  for (int i = tid; i < 256 * 32; i += 512) {
    const int idx = i >> 5;
    const float v = exp2f((idx + 0.5f) * (1.f / 256.f) + 0.125f);
    const int target = (v < 2.f) ? (int)rintf(128.f * v) - 128 : (int)rintf(64.f * v);
    reinterpret_cast<uint32_t*>(sm0 + LUT)[i] = (uint32_t)(target - (idx >> 1)) << 16;
  }
  for (int i = tid; i < S_; i += 512) {
    const uint32_t mask = ((i >> 6) & 1) ? LUT_MASK_ODD : LUT_MASK_EVEN;
    const uint32_t o = ((mask >> ((i >> 3) & 7)) & 1) ? 0xBF80BF80u : 0x3F803F80u;
    *reinterpret_cast<uint4*>(sm0 + VS + 65536 + i * 16) = make_uint4(o, o, o, o);
  }
  fence_async_smem();
  __syncthreads();
  pdl_wait();
  if (tid < 256 && lane == 0) {
    const int c = tid >> 5;
    const uint32_t b = bars + c * 8;
    mbar_expect(b, 16384);
    bulk_g2s(KS + c * 8192, g_K + c * 8192, 8192, b);
    bulk_g2s(VS + c * 4096, g_V + c * 4096, 4096, b);
    bulk_g2s(VS + 32768 + c * 4096, g_V + 32768 + c * 4096, 4096, b);
  }
  {
    float m = __ldcg(g_kmax + tid);
    m = fmaxf(m, __shfl_xor_sync(~0u, m, 16));
    if (lane < 16) reinterpret_cast<float*>(sm0 + kred)[(tid >> 5) * 16 + lane] = m;
  }
  const int g = lane >> 2, t = lane & 3;
  uint32_t qq[2][4];
#pragma unroll
  for (int tile = 0; tile < 2; tile++) {
    const int row0 = (blockIdx.x * 8 + wg * 2 + tile) * 64 + warp * 16 + g;
    const uint32_t* qp = reinterpret_cast<const uint32_t*>(g_Q);
    qq[tile][0] = __ldcg(qp + (size_t)row0 * 8 + t);
    qq[tile][1] = __ldcg(qp + (size_t)(row0 + 8) * 8 + t);
    qq[tile][2] = __ldcg(qp + (size_t)row0 * 8 + 4 + t);
    qq[tile][3] = __ldcg(qp + (size_t)(row0 + 8) * 8 + 4 + t);
  }
  __syncthreads();
  float km[4];
  {
    const float* kr = reinterpret_cast<const float*>(sm0 + kred);
    km[0] = km[1] = km[2] = km[3] = 0.f;
#pragma unroll
    for (int w = 0; w < 16; w++) {
      km[0] = fmaxf(km[0], kr[w * 16 + 2 * t]); km[1] = fmaxf(km[1], kr[w * 16 + 2 * t + 1]);
      km[2] = fmaxf(km[2], kr[w * 16 + 2 * t + 8]); km[3] = fmaxf(km[3], kr[w * 16 + 2 * t + 9]);
    }
  }
  uint32_t unsafe_bits = 0;
#pragma unroll
  for (int tile = 0; tile < 2; tile++) {
    const uint32_t* q = qq[tile];
    float b0 = fabsf(bf_lo(q[0])) * km[0] + fabsf(bf_hi(q[0])) * km[1] + fabsf(bf_lo(q[2])) * km[2] + fabsf(bf_hi(q[2])) * km[3];
    float b1 = fabsf(bf_lo(q[1])) * km[0] + fabsf(bf_hi(q[1])) * km[1] + fabsf(bf_lo(q[3])) * km[2] + fabsf(bf_hi(q[3])) * km[3];
    b0 += __shfl_xor_sync(~0u, b0, 1); b0 += __shfl_xor_sync(~0u, b0, 2);
    b1 += __shfl_xor_sync(~0u, b1, 1); b1 += __shfl_xor_sync(~0u, b1, 2);
    const uint32_t bad = !(b0 <= SAFE_SCORE_BOUND && b1 <= SAFE_SCORE_BOUND);
    uint32_t u;
    asm volatile("{.reg .pred p, r; setp.ne.u32 p, %1, 0; bar.red.or.pred r, %2, 128, p; selp.u32 %0, 1, 0, r;}"
                 : "=r"(u) : "r"(bad), "r"(1 + wg) : "memory");
    unsafe_bits |= u << tile;
    asm volatile("st.shared.v4.u32 [%0], {%1,%2,%3,%4};" ::"r"(sbase + 2048 + tile * 8192 + tid * 16), "r"(q[0]), "r"(q[1]), "r"(q[2]), "r"(q[3]) : "memory");
  }
  const uint32_t lutlane = LUT | (lane * 4);
  constexpr uint64_t KSTEP = (64 * 32) >> 4, VSTEP = (16 * 16) >> 4;
#pragma unroll 1
  for (int tile = 0; tile < 2; tile++) {
    uint32_t q[4];
    asm volatile("ld.shared.v4.u32 {%0,%1,%2,%3}, [%4];" : "=r"(q[0]), "=r"(q[1]), "=r"(q[2]), "=r"(q[3]) : "r"(sbase + 2048 + tile * 8192 + tid * 16) : "memory");
    const uint32_t unsafe = (unsafe_bits >> tile) & 1;
    float o[12];
#pragma unroll
    for (int i = 0; i < 12; i++) o[i] = 0.f;
    uint64_t kd = mkdesc(KS, 128, 256, 0);
    uint64_t vd = mkdesc(VS, 128, 32768, 0);
    if (!unsafe) {
      float s[32];
      uint32_t p[16];
      mbar_wait(bars, 0);
      fence_regs<12>(o);
      wg_fence();
      wgmma_rs_n64(s, q[0], q[1], q[2], q[3], kd, 0); kd += KSTEP;
      wg_commit();
#pragma unroll 1
      for (int j = 0; j < 32; j += 2) {
        wg_wait<0>(); fence_regs<32>(s); fence_regs<12>(o); fence_regs_u<16>(p);
        if ((j & 3) == 2 && j < 30) mbar_wait(bars + ((j + 2) >> 2) * 8, 0);
        exp_pack<LUT_MASK_EVEN>(s, p, lutlane);
        wg_fence();
#pragma unroll
        for (int k = 0; k < 4; k++) { wgmma_rs_tb_n24(o, p[4 * k], p[4 * k + 1], p[4 * k + 2], p[4 * k + 3], vd, 1); vd += VSTEP; }
        wgmma_rs_n64(s, q[0], q[1], q[2], q[3], kd, 0); kd += KSTEP;
        wg_commit();
        wg_wait<0>(); fence_regs<32>(s); fence_regs<12>(o); fence_regs_u<16>(p);
        exp_pack<LUT_MASK_ODD>(s, p, lutlane);
        wg_fence();
#pragma unroll
        for (int k = 0; k < 4; k++) { wgmma_rs_tb_n24(o, p[4 * k], p[4 * k + 1], p[4 * k + 2], p[4 * k + 3], vd, 1); vd += VSTEP; }
        wgmma_rs_n64(s, q[0], q[1], q[2], q[3], kd, 0); kd += KSTEP;
        wg_commit();
      }
      wg_wait<0>(); fence_regs<12>(o); fence_regs<32>(s);
    } else {
      for (int c = 0; c < 8; c++) mbar_wait(bars + c * 8, 0);
      float m0 = -INFINITY, m1 = -INFINITY;
#pragma unroll 1
      for (int kb = 0; kb < S_ / 16; kb++) {
        uint32_t kf[4];
        float sa[4] = {0.f, 0.f, 0.f, 0.f}, sc[4] = {0.f, 0.f, 0.f, 0.f};
        ldsm4(kf, KS + kb * 512 + lane * 16);
        mma16816(sa, q, kf[0], kf[1]);
        mma16816(sc, q, kf[2], kf[3]);
        m0 = fmaxf(fmaxf(m0, fmaxf(sa[0], sa[1])), fmaxf(sc[0], sc[1]));
        m1 = fmaxf(fmaxf(m1, fmaxf(sa[2], sa[3])), fmaxf(sc[2], sc[3]));
      }
      m0 = fmaxf(m0, __shfl_xor_sync(~0u, m0, 1)); m0 = fmaxf(m0, __shfl_xor_sync(~0u, m0, 2));
      m1 = fmaxf(m1, __shfl_xor_sync(~0u, m1, 1)); m1 = fmaxf(m1, __shfl_xor_sync(~0u, m1, 2));
#pragma unroll 1
      for (int kb = 0; kb < S_ / 16; kb++) {
        uint32_t kf[4], vf[4], ef[4], a[4];
        float sa[4] = {0.f, 0.f, 0.f, 0.f}, sc[4] = {0.f, 0.f, 0.f, 0.f};
        ldsm4(kf, KS + kb * 512 + lane * 16);
        const uint32_t krow = (kb * 16 + (lane & 15)) * 16;
        ldsm4t(vf, VS + (lane >> 4) * 32768 + krow);
        ldsm4t(ef, VS + 65536 + krow);
        mma16816(sa, q, kf[0], kf[1]);
        mma16816(sc, q, kf[2], kf[3]);
        const uint32_t mask = ((kb >> 2) & 1) ? LUT_MASK_ODD : LUT_MASK_EVEN;
        const uint32_t sg0 = ((mask >> ((2 * kb) & 7)) & 1) ? 0x80008000u : 0u, sg1 = ((mask >> ((2 * kb + 1) & 7)) & 1) ? 0x80008000u : 0u;
        a[0] = pack_bf16(ex2f(sa[0] - m0), ex2f(sa[1] - m0)) ^ sg0;
        a[1] = pack_bf16(ex2f(sa[2] - m1), ex2f(sa[3] - m1)) ^ sg0;
        a[2] = pack_bf16(ex2f(sc[0] - m0), ex2f(sc[1] - m0)) ^ sg1;
        a[3] = pack_bf16(ex2f(sc[2] - m1), ex2f(sc[3] - m1)) ^ sg1;
        mma16816(o, a, vf[0], vf[1]);
        mma16816(o + 4, a, vf[2], vf[3]);
        mma16816(o + 8, a, ef[0], ef[1]);
      }
    }
    const float r0 = 1.f / o[8], r1 = 1.f / o[10];
    const int row0 = (blockIdx.x * 8 + wg * 2 + tile) * 64 + warp * 16 + g;
    uint32_t* op = reinterpret_cast<uint32_t*>(g_O);
    op[(size_t)row0 * 8 + t] = pack_bf16(o[0] * r0, o[1] * r0);
    op[(size_t)(row0 + 8) * 8 + t] = pack_bf16(o[2] * r1, o[3] * r1);
    op[(size_t)row0 * 8 + 4 + t] = pack_bf16(o[4] * r0, o[5] * r0);
    op[(size_t)(row0 + 8) * 8 + 4 + t] = pack_bf16(o[6] * r1, o[7] * r1);
  }
}

__device__ __forceinline__ void residual_block(const float* a, uint32_t tile, int warp, int lane, float2* stat_out  ) {
  const int rl = warp * 16 + ((lane >> 3) & 1) * 8 + (lane & 7);
  const uint32_t rowa = tile + rl * 128;
  float s0 = 0.f, q0 = 0.f, s1 = 0.f, q1 = 0.f;
#pragma unroll
  for (int j = 0; j < 8; j += 2) {
    const uint32_t ad = rowa + (((j + (lane >> 4)) ^ (rl & 7)) << 4);
    uint32_t r[4];
    ldsm4(r, ad);
    const float* c = a + 4 * j;
    const uint32_t u0 = pack_bf16(bf_lo(r[0]) + c[0], bf_hi(r[0]) + c[1]);
    const uint32_t u1 = pack_bf16(bf_lo(r[1]) + c[2], bf_hi(r[1]) + c[3]);
    const uint32_t u2 = pack_bf16(bf_lo(r[2]) + c[4], bf_hi(r[2]) + c[5]);
    const uint32_t u3 = pack_bf16(bf_lo(r[3]) + c[6], bf_hi(r[3]) + c[7]);
    s0 += (bf_lo(u0) + bf_hi(u0)) + (bf_lo(u2) + bf_hi(u2));
    q0 += bf_lo(u0) * bf_lo(u0) + bf_hi(u0) * bf_hi(u0) + bf_lo(u2) * bf_lo(u2) + bf_hi(u2) * bf_hi(u2);
    s1 += (bf_lo(u1) + bf_hi(u1)) + (bf_lo(u3) + bf_hi(u3));
    q1 += bf_lo(u1) * bf_lo(u1) + bf_hi(u1) * bf_hi(u1) + bf_lo(u3) * bf_lo(u3) + bf_hi(u3) * bf_hi(u3);
    stsm4(ad, u0, u1, u2, u3);
  }
#pragma unroll
  for (int o = 1; o < 4; o <<= 1) {
    s0 += __shfl_xor_sync(~0u, s0, o); q0 += __shfl_xor_sync(~0u, q0, o);
    s1 += __shfl_xor_sync(~0u, s1, o); q1 += __shfl_xor_sync(~0u, q1, o);
  }
  if ((lane & 3) == 0) {
    stat_out[0] = make_float2(s0, q0);
    stat_out[8 * 8] = make_float2(s1, q1);
  }
}

constexpr int OPJ_SMEM = 8 * 24576 + 16384 + 1024 + 256;
__global__ void __launch_bounds__(160, 1) oproj_kernel(const __grid_constant__ CUtensorMap mA, const __grid_constant__ CUtensorMap mW,
                                                        const __grid_constant__ CUtensorMap mRes, const __grid_constant__ CUtensorMap mOut) {
  extern __shared__ uint8_t smraw[];
  const uint32_t sb = (smem_u32(smraw) + 1023) & ~1023u;
  const uint32_t res = sb + 8 * 24576, bars = res + 16384;
  const int tid = threadIdx.x, lane = tid & 31, warp = tid >> 5;
  const int tb = blockIdx.x >> 2, ct = blockIdx.x & 3;
  pdl_trigger();
  if (tid == 0) {
    for (int i = 0; i < 9; i++) mbar_init(bars + i * 8, 1);
    mbar_fence_init();
  }
  __syncthreads();
  if (warp == 4) {
    if (lane == 0) {
#pragma unroll 1
      for (int kc = 0; kc < 8; kc++) {
        mbar_expect(bars + kc * 8, 24576);
        tma3d(sb + kc * 24576 + 8192, &mW, 0, kc * 64, ct * 2, bars + kc * 8);
      }
      pdl_wait();
#pragma unroll 1
      for (int kc = 0; kc < 8; kc++) tma2d(sb + kc * 24576, &mA, kc * 64, tb * 64, bars + kc * 8);
      mbar_expect(bars + 64, 16384);
      tma2d(res, &mRes, ct * 128, tb * 64, bars + 64);
      tma2d(res + 8192, &mRes, ct * 128 + 64, tb * 64, bars + 64);
    }
    return;
  }
  float acc[64];
#pragma unroll
  for (int i = 0; i < 64; i++) acc[i] = 0.f;
  fence_regs<64>(acc);
#pragma unroll 1
  for (int kc = 0; kc < 8; kc++) {
    const uint32_t st = sb + kc * 24576;
    mbar_wait(bars + kc * 8, 0);
    wg_fence();
#pragma unroll
    for (int ks = 0; ks < 4; ks++)
      wgmma_ss_tb_n128(acc, mkdesc(st + ks * 32, 16, 1024, 1), mkdesc(st + 8192 + ks * 2048, 8192, 1024, 1), 1);
    wg_commit();
  }
  wg_wait<0>();
  fence_regs<64>(acc);
  pdl_wait();
  mbar_wait(bars + 64, 0);
  const int r0 = tb * 64 + warp * 16 + (lane >> 2);
  residual_block(acc, res, warp, lane, g_statB + r0 * 8 + ct * 2);
  residual_block(acc + 32, res + 8192, warp, lane, g_statB + r0 * 8 + ct * 2 + 1);
  fence_async_smem();
  bar_sync(1, 128);
  if (tid == 0) {
    tma2d_store(&mOut, ct * 128, tb * 64, res);
    tma2d_store(&mOut, ct * 128 + 64, tb * 64, res + 8192);
    bulk_commit_wait_all();
  }
}

constexpr int F1_STAGES = 5, F1_A = 16384, F1_B = 28672, F1_STAGE = F1_A + F1_B;
constexpr int F1_SMEM = F1_STAGES * F1_STAGE + 1024 + 256;
__global__ void __launch_bounds__(288, 1) ffn1_kernel(const __grid_constant__ CUtensorMap mA, const __grid_constant__ CUtensorMap mW,
                                                       const __grid_constant__ CUtensorMap mH) {
  extern __shared__ uint8_t smraw[];
  const uint32_t sb = (smem_u32(smraw) + 1023) & ~1023u;
  const uint32_t bars = sb + F1_STAGES * F1_STAGE;
  const int tid = threadIdx.x, lane = tid & 31, warp = tid >> 5;
  const int mb = blockIdx.x >> 3, fs = blockIdx.x & 7;
  pdl_trigger();
  if (tid == 0) {
    for (int i = 0; i < F1_STAGES; i++) { mbar_init(bars + i * 8, 1); mbar_init(bars + (F1_STAGES + i) * 8, 8); }
    mbar_fence_init();
  }
  __syncthreads();
  if (warp == 8) {
    if (lane == 0) {
#pragma unroll 1
      for (int kc = 0; kc < F1_STAGES; kc++) {
        mbar_expect(bars + kc * 8, F1_STAGE);
        tma3d(sb + kc * F1_STAGE + F1_A, &mW, 0, kc * 64, fs * 7, bars + kc * 8);
      }
      pdl_wait();
#pragma unroll 1
      for (int kc = 0; kc < F1_STAGES; kc++) tma2d(sb + kc * F1_STAGE, &mA, kc * 64, mb * 128, bars + kc * 8);
#pragma unroll 1
      for (int kc = F1_STAGES; kc < 8; kc++) {
        const int s = kc - F1_STAGES;
        mbar_wait(bars + (F1_STAGES + s) * 8, 0);
        mbar_expect(bars + s * 8, F1_STAGE);
        tma2d(sb + s * F1_STAGE, &mA, kc * 64, mb * 128, bars + s * 8);
        tma3d(sb + s * F1_STAGE + F1_A, &mW, 0, kc * 64, fs * 7, bars + s * 8);
      }
    }
    return;
  }
  const int wg = warp >> 2, w4 = warp & 3;
  float acc[112];
#pragma unroll
  for (int i = 0; i < 112; i++) acc[i] = 0.f;
  fence_regs<112>(acc);
#pragma unroll 1
  for (int kc = 0; kc < 8; kc++) {
    const int s = kc % F1_STAGES;
    const uint32_t st = sb + s * F1_STAGE;
    mbar_wait(bars + s * 8, kc / F1_STAGES);
    wg_fence();
#pragma unroll
    for (int ks = 0; ks < 4; ks++)
      wgmma_ss_tb_n224(acc, mkdesc(st + wg * 8192 + ks * 32, 16, 1024, 1), mkdesc(st + F1_A + ks * 1024, 4096, 512, 2), 1);
    wg_commit();
    if (kc >= 1 && kc - 1 < 8 - F1_STAGES) {
      wg_wait<1>();
      if (lane == 0) mbar_arrive(bars + (F1_STAGES + kc - 1) * 8);
    }
  }
  wg_wait<0>();
  fence_regs<112>(acc);
  pdl_wait();
  const int g = lane >> 2, t = lane & 3;
  const int r0 = mb * 128 + wg * 64 + w4 * 16 + g;
  float mean0, rstd0, mean1, rstd1;
  row_stats(g_statB, r0, mean0, rstd0);
  row_stats(g_statB, r0 + 8, mean1, rstd1);
  bar_sync(1, 256);
  const uint32_t stg = sb + wg * 28672;
  const int rl = w4 * 16 + ((lane >> 3) & 1) * 8 + (lane & 7);
  constexpr float NL2E = -1.4426950408889634f;
#pragma unroll
  for (int j = 0; j < 28; j += 2) {
    const float2 ca = __ldcg(reinterpret_cast<const float2*>(g_cs1 + fs * 224 + 8 * j + 2 * t));
    const float2 cb = __ldcg(reinterpret_cast<const float2*>(g_cs1 + fs * 224 + 8 * j + 8 + 2 * t));
    const float* a = acc + 4 * j;
    float z[8];
    z[0] = (a[0] - mean0 * ca.x) * rstd0; z[1] = (a[1] - mean0 * ca.y) * rstd0;
    z[2] = (a[2] - mean1 * ca.x) * rstd1; z[3] = (a[3] - mean1 * ca.y) * rstd1;
    z[4] = (a[4] - mean0 * cb.x) * rstd0; z[5] = (a[5] - mean0 * cb.y) * rstd0;
    z[6] = (a[6] - mean1 * cb.x) * rstd1; z[7] = (a[7] - mean1 * cb.y) * rstd1;
#pragma unroll
    for (int i = 0; i < 8; i++) z[i] = __fdividef(z[i], 1.f + ex2f(z[i] * NL2E));
    const int blk = j >> 2, ch = (j & 3) + (lane >> 4);
    stsm4(stg + blk * 4096 + rl * 64 + ((ch ^ ((rl >> 1) & 3)) << 4), pack_bf16(z[0], z[1]), pack_bf16(z[2], z[3]), pack_bf16(z[4], z[5]),
          pack_bf16(z[6], z[7]));
  }
  fence_async_smem();
  bar_sync(2 + wg, 128);
  if ((tid & 127) == 0) {
    tma3d_store(&mH, 0, mb * 128 + wg * 64, fs * 7, stg);
    bulk_commit_wait_all();
  }
}

constexpr int F2_STAGES = 5, F2_STAGE = 32768;
constexpr int F2_SMEM = F2_STAGES * F2_STAGE + 16384 + 32768 + 1024 + 256;
__global__ void __cluster_dims__(2, 1, 1) __launch_bounds__(288, 1)
ffn2_kernel(const __grid_constant__ CUtensorMap mA, const __grid_constant__ CUtensorMap mW, const __grid_constant__ CUtensorMap mRes,
            const __grid_constant__ CUtensorMap mOut, float2* __restrict__ stat) {
  extern __shared__ uint8_t smraw[];
  const uint32_t sb = (smem_u32(smraw) + 1023) & ~1023u;
  const uint32_t res = sb + F2_STAGES * F2_STAGE, recv = res + 16384, bars = recv + 32768;
  const int tid = threadIdx.x, lane = tid & 31, warp = tid >> 5;
  const int mb = blockIdx.x >> 3, nt = (blockIdx.x & 7) >> 1, kh = blockIdx.x & 1;
  pdl_trigger();
  if (tid == 0) {
    for (int i = 0; i < F2_STAGES; i++) { mbar_init(bars + i * 8, 1); mbar_init(bars + (F2_STAGES + i) * 8, 8); }
    mbar_init(bars + 2 * F2_STAGES * 8, 1);
    mbar_fence_init();
  }
  __syncthreads();
  if (warp == 8) {
    if (lane == 0) {
#pragma unroll 1
      for (int kc = 0; kc < F2_STAGES; kc++) {
        mbar_expect(bars + kc * 8, F2_STAGE);
        tma3d(sb + kc * F2_STAGE + 16384, &mW, 0, kh * 896 + kc * 64, nt * 2, bars + kc * 8);
      }
      pdl_wait();
#pragma unroll 1
      for (int kc = 0; kc < F2_STAGES; kc++) tma2d(sb + kc * F2_STAGE, &mA, kh * 896 + kc * 64, mb * 128, bars + kc * 8);
      mbar_expect(bars + 2 * F2_STAGES * 8, 16384);
      tma2d(res, &mRes, nt * 128 + kh * 64, mb * 128, bars + 2 * F2_STAGES * 8);
      tma2d(res + 8192, &mRes, nt * 128 + kh * 64, mb * 128 + 64, bars + 2 * F2_STAGES * 8);
      int s = 0, ph = 0;
#pragma unroll 1
      for (int kc = F2_STAGES; kc < 14; kc++) {
        mbar_wait(bars + (F2_STAGES + s) * 8, ph);
        mbar_expect(bars + s * 8, F2_STAGE);
        tma2d(sb + s * F2_STAGE, &mA, kh * 896 + kc * 64, mb * 128, bars + s * 8);
        tma3d(sb + s * F2_STAGE + 16384, &mW, 0, kh * 896 + kc * 64, nt * 2, bars + s * 8);
        if (++s == F2_STAGES) { s = 0; ph ^= 1; }
      }
    }
    return;
  }
  const int wg = warp >> 2, w4 = warp & 3;
  float acc[64];
#pragma unroll
  for (int i = 0; i < 64; i++) acc[i] = 0.f;
  fence_regs<64>(acc);
  {
    int s = 0, ph = 0, ps = 0;
#pragma unroll 1
    for (int kc = 0; kc < 14; kc++) {
      const uint32_t st = sb + s * F2_STAGE;
      mbar_wait(bars + s * 8, ph);
      wg_fence();
#pragma unroll
      for (int ks = 0; ks < 4; ks++)
        wgmma_ss_tb_n128(acc, mkdesc(st + wg * 8192 + ks * 32, 16, 1024, 1), mkdesc(st + 16384 + ks * 2048, 8192, 1024, 1), 1);
      wg_commit();
      if (kc >= 1) {
        wg_wait<1>();
        if (lane == 0) mbar_arrive(bars + (F2_STAGES + ps) * 8);
      }
      ps = s;
      if (++s == F2_STAGES) { s = 0; ph ^= 1; }
    }
  }
  wg_wait<0>();
  fence_regs<64>(acc);
  {
    uint32_t dst;
    asm volatile("mapa.shared::cluster.u32 %0, %1, %2;" : "=r"(dst) : "r"(recv + wg * 16384 + (tid & 127) * 16), "r"(kh ^ 1));
#pragma unroll
    for (int i = 0; i < 8; i++) {
      const float x0 = kh ? acc[4 * i] : acc[32 + 4 * i], x1 = kh ? acc[4 * i + 1] : acc[33 + 4 * i];
      const float x2 = kh ? acc[4 * i + 2] : acc[34 + 4 * i], x3 = kh ? acc[4 * i + 3] : acc[35 + 4 * i];
      asm volatile("st.shared::cluster.v4.f32 [%0], {%1,%2,%3,%4};" ::"r"(dst + i * 2048), "f"(x0), "f"(x1), "f"(x2), "f"(x3) : "memory");
    }
  }
  asm volatile("barrier.cluster.arrive.release.aligned;" ::: "memory");
  asm volatile("barrier.cluster.wait.acquire.aligned;" ::: "memory");
  float fin[32];
#pragma unroll
  for (int i = 0; i < 8; i++) {
    float4 v;
    asm volatile("ld.shared.v4.f32 {%0,%1,%2,%3}, [%4];" : "=f"(v.x), "=f"(v.y), "=f"(v.z), "=f"(v.w) : "r"(recv + wg * 16384 + (tid & 127) * 16 + i * 2048));
    fin[4 * i] = v.x + (kh ? acc[32 + 4 * i] : acc[4 * i]);
    fin[4 * i + 1] = v.y + (kh ? acc[33 + 4 * i] : acc[4 * i + 1]);
    fin[4 * i + 2] = v.z + (kh ? acc[34 + 4 * i] : acc[4 * i + 2]);
    fin[4 * i + 3] = v.w + (kh ? acc[35 + 4 * i] : acc[4 * i + 3]);
  }
  pdl_wait();
  mbar_wait(bars + 2 * F2_STAGES * 8, 0);
  const int r0 = mb * 128 + wg * 64 + w4 * 16 + (lane >> 2);
  residual_block(fin, res + wg * 8192, w4, lane, stat + r0 * 8 + nt * 2 + kh);
  fence_async_smem();
  bar_sync(2 + wg, 128);
  if ((tid & 127) == 0) {
    tma2d_store(&mOut, nt * 128 + kh * 64, mb * 128 + wg * 64, res + wg * 8192);
    bulk_commit_wait_all();
  }
}

typedef CUresult (*EncodeFn)(CUtensorMap*, CUtensorMapDataType, cuuint32_t, void*, const cuuint64_t*, const cuuint64_t*, const cuuint32_t*,
                             const cuuint32_t*, CUtensorMapInterleave, CUtensorMapSwizzle, CUtensorMapL2promotion, CUtensorMapFloatOOBfill);

CUtensorMap make_map(EncodeFn fn, const void* base, int rank, const cuuint64_t* dims, const cuuint64_t* strides, const cuuint32_t* box,
                     CUtensorMapSwizzle swz) {
  CUtensorMap m;
  cuuint32_t es[3] = {1, 1, 1};
  fn(&m, CU_TENSOR_MAP_DATA_TYPE_BFLOAT16, rank, const_cast<void*>(base), dims, strides, box, es, CU_TENSOR_MAP_INTERLEAVE_NONE, swz,
     CU_TENSOR_MAP_L2_PROMOTION_L2_256B, CU_TENSOR_MAP_FLOAT_OOB_FILL_NONE);
  return m;
}
CUtensorMap map2d(EncodeFn fn, const void* base, int rows, int cols, int box_rows) {
  cuuint64_t dims[2] = {(cuuint64_t)cols, (cuuint64_t)rows}, strides[1] = {(cuuint64_t)cols * 2};
  cuuint32_t box[2] = {64, (cuuint32_t)box_rows};
  return make_map(fn, base, 2, dims, strides, box, CU_TENSOR_MAP_SWIZZLE_128B);
}
CUtensorMap map3d(EncodeFn fn, const void* base, int rows, int cols, int inner, int box_rows, int box_blocks) {
  cuuint64_t dims[3] = {(cuuint64_t)inner, (cuuint64_t)rows, (cuuint64_t)(cols / inner)};
  cuuint64_t strides[2] = {(cuuint64_t)cols * 2, (cuuint64_t)inner * 2};
  cuuint32_t box[3] = {(cuuint32_t)inner, (cuuint32_t)box_rows, (cuuint32_t)box_blocks};
  return make_map(fn, base, 3, dims, strides, box, inner == 64 ? CU_TENSOR_MAP_SWIZZLE_128B : CU_TENSOR_MAP_SWIZZLE_64B);
}

template <typename... KArgs, typename... Args>
void launch(void (*kern)(KArgs...), int grid, int block, int smem, bool pdl, Args... args) {
  cudaLaunchConfig_t cfg = {};
  cfg.gridDim = dim3(grid);
  cfg.blockDim = dim3(block);
  cfg.dynamicSmemBytes = smem;
  cfg.stream = cudaStreamPerThread;
  cudaLaunchAttribute at[1];
  at[0].id = cudaLaunchAttributeProgrammaticStreamSerialization;
  at[0].val.programmaticStreamSerializationAllowed = 1;
  cfg.attrs = at;
  cfg.numAttrs = pdl ? 1 : 0;
  cudaLaunchKernelEx(&cfg, kern, args...);
}

}

extern "C" void kernel_launch(void* const* d_in, const int* in_sizes, int n_in, void* d_out, int out_size) {
  const bf16* x = (const bf16*)d_in[0];
  const bf16* wq = (const bf16*)d_in[1];
  const bf16* wk = (const bf16*)d_in[2];
  const bf16* wv = (const bf16*)d_in[3];
  const bf16* wo = (const bf16*)d_in[4];
  const bf16* w1 = (const bf16*)d_in[6];
  const bf16* w2 = (const bf16*)d_in[7];

  void* fp = nullptr;
  cudaDriverEntryPointQueryResult qr;
  cudaGetDriverEntryPoint("cuTensorMapEncodeTiled", &fp, cudaEnableDefault, &qr);
  EncodeFn fn = (EncodeFn)fp;
  void *pO, *pX1, *pX2, *pH, *pSA;
  cudaGetSymbolAddress(&pO, g_O);
  cudaGetSymbolAddress(&pX1, g_x1);
  cudaGetSymbolAddress(&pX2, g_x2);
  cudaGetSymbolAddress(&pH, g_h);
  cudaGetSymbolAddress(&pSA, g_statA);

  const CUtensorMap mX0 = map2d(fn, x, S_, D_, 64), mX2 = map2d(fn, pX2, S_, D_, 64), mOutM = map2d(fn, d_out, S_, D_, 64);
  const CUtensorMap mO = map2d(fn, pO, S_, D_, 64), mX1 = map2d(fn, pX1, S_, D_, 64), mX1_128 = map2d(fn, pX1, S_, D_, 128);
  const CUtensorMap mH128 = map2d(fn, pH, S_, F_, 128), mHst = map3d(fn, pH, S_, F_, 32, 64, 7);
  const CUtensorMap mWq = map3d(fn, wq, D_, D_, 64, 64, 2), mWo = map3d(fn, wo, D_, D_, 64, 64, 2);
  const CUtensorMap mWk = map2d(fn, wk, D_, 16, 64), mWv = map2d(fn, wv, D_, 16, 64);
  const CUtensorMap mW1 = map3d(fn, w1, D_, F_, 32, 64, 7), mW2 = map3d(fn, w2, F_, D_, 64, 64, 2);

  cudaFuncSetAttribute(qkv_kernel<true>, cudaFuncAttributeMaxDynamicSharedMemorySize, QKV_SMEM);
  cudaFuncSetAttribute(qkv_kernel<false>, cudaFuncAttributeMaxDynamicSharedMemorySize, QKV_SMEM);
  cudaFuncSetAttribute(attn_kernel, cudaFuncAttributeMaxDynamicSharedMemorySize, ATT_SMEM);
  cudaFuncSetAttribute(oproj_kernel, cudaFuncAttributeMaxDynamicSharedMemorySize, OPJ_SMEM);
  cudaFuncSetAttribute(ffn1_kernel, cudaFuncAttributeMaxDynamicSharedMemorySize, F1_SMEM);
  cudaFuncSetAttribute(ffn2_kernel, cudaFuncAttributeMaxDynamicSharedMemorySize, F2_SMEM);

  launch(prep_kernel, 128, 256, 0, false, x, wq, wk, wv, w1, wo, w2);
  for (int layer = 0; layer < 2; layer++) {
    if (layer == 0) launch(qkv_kernel<true>, 128, 160, QKV_SMEM, true, mX0, mWq, mWk, mWv);
    else launch(qkv_kernel<false>, 128, 160, QKV_SMEM, true, mX2, mWq, mWk, mWv);
    launch(attn_kernel, 128, 512, ATT_SMEM, true);
    launch(oproj_kernel, 128, 160, OPJ_SMEM, true, mO, mWo, layer == 0 ? mX0 : mX2, mX1);
    launch(ffn1_kernel, 128, 288, F1_SMEM, true, mX1_128, mW1, mHst);
    launch(ffn2_kernel, 128, 288, F2_SMEM, true, mH128, mW2, mX1, layer == 0 ? mX2 : mOutM, (float2*)pSA);
  }
}
```

```cpp
#include <cuda_runtime.h>
#include <cuda_bf16.h>
#include <cuda.h>
#include <stdint.h>

namespace {

typedef __nv_bfloat16 bf16;
constexpr int S_ = 2048, D_ = 512, F_ = 1792;
constexpr float LN_EPS = 1e-5f;
constexpr float QSCALE = 0.25f * 1.4426950408889634f;

constexpr uint32_t LUT_MASK_EVEN = 0x55, LUT_MASK_ODD = 0x5D;
constexpr float SAFE_SCORE_BOUND = 80.0f;

__device__ __align__(1024) bf16 g_Q[S_ * D_];
__device__ __align__(1024) uint8_t g_KV[S_ * 64];
__device__ __align__(1024) float g_kmax[32 * 16];
__device__ __align__(1024) uint8_t g_x0T[S_ * D_ * 2];
__device__ __align__(1024) uint8_t g_OT[S_ * D_ * 2];
__device__ __align__(1024) uint8_t g_x1T[S_ * D_ * 2];
__device__ __align__(1024) uint8_t g_x2T[S_ * D_ * 2];
__device__ __align__(1024) uint8_t g_hT[S_ * F_ * 2];
__device__ __align__(1024) float2 g_statA[S_ * 8];
__device__ __align__(1024) float2 g_statB[S_ * 8];
__device__ __align__(1024) float g_csQKV[4 * 136];
__device__ __align__(1024) float g_cs1[F_];
__device__ __align__(1024) uint8_t g_Wqkvp[4 * 8 * 17408];
__device__ __align__(1024) uint8_t g_Wop[4 * 8 * 16384];
__device__ __align__(1024) uint8_t g_W1p[8 * 8 * 28672];
__device__ __align__(1024) uint8_t g_W2p[4 * 28 * 16384];
__device__ unsigned g_pack_done;
constexpr unsigned NPACK = 4;

#define TS(kid, slot)
#define GT(i)
__device__ __forceinline__ uint32_t smem_u32(const void* p) { return (uint32_t)__cvta_generic_to_shared(p); }
__device__ __forceinline__ void mbar_init(uint32_t b, uint32_t c) { asm volatile("mbarrier.init.shared::cta.b64 [%0], %1;" ::"r"(b), "r"(c)); }
__device__ __forceinline__ void mbar_fence_init() { asm volatile("fence.mbarrier_init.release.cluster;" ::: "memory"); }
__device__ __forceinline__ void mbar_expect(uint32_t b, uint32_t bytes) {
  asm volatile("mbarrier.arrive.expect_tx.shared::cta.b64 _, [%0], %1;" ::"r"(b), "r"(bytes) : "memory");
}
__device__ __forceinline__ void mbar_arrive(uint32_t b) { asm volatile("mbarrier.arrive.shared::cta.b64 _, [%0];" ::"r"(b) : "memory"); }
__device__ __forceinline__ void mbar_wait(uint32_t b, uint32_t ph) {
  asm volatile(
      "{.reg .pred p;\n"
      "LAB_WAIT:\n"
      "mbarrier.try_wait.parity.shared::cta.b64 p, [%0], %1;\n"
      "@p bra LAB_DONE;\n"
      "bra LAB_WAIT;\n"
      "LAB_DONE:\n}" ::"r"(b), "r"(ph) : "memory");
}
__device__ __forceinline__ void bulk_g2s(uint32_t dst, const void* src, uint32_t bytes, uint32_t bar) {
  asm volatile("cp.async.bulk.shared::cluster.global.mbarrier::complete_tx::bytes [%0], [%1], %2, [%3];" ::"r"(dst), "l"(src), "r"(bytes), "r"(bar) : "memory");
}
__device__ __forceinline__ void bulk_s2g(void* dst, uint32_t src, uint32_t bytes) {
  asm volatile("cp.async.bulk.global.shared::cta.bulk_group [%0], [%1], %2;" ::"l"(dst), "r"(src), "r"(bytes) : "memory");
}
__device__ __forceinline__ void cp_async16(uint32_t dst, const void* src) {
  asm volatile("cp.async.cg.shared.global [%0], [%1], 16;" ::"r"(dst), "l"(src) : "memory");
}
__device__ __forceinline__ bool pack_ready() {
  unsigned v;
  asm volatile("ld.acquire.gpu.global.u32 %0, [%1];" : "=r"(v) : "l"(&g_pack_done) : "memory");
  return v == NPACK;
}
__device__ __forceinline__ void tma2d_store(const CUtensorMap* m, int c0, int c1, uint32_t src) {
  asm volatile("cp.async.bulk.tensor.2d.global.shared::cta.bulk_group [%0, {%2, %3}], [%1];" ::"l"(m), "r"(src), "r"(c0), "r"(c1) : "memory");
}
__device__ __forceinline__ void bulk_commit_wait_all() {
  asm volatile("cp.async.bulk.commit_group;" ::: "memory");
  asm volatile("cp.async.bulk.wait_group 0;" ::: "memory");
}
__device__ __forceinline__ void fence_async_smem() { asm volatile("fence.proxy.async.shared::cta;" ::: "memory"); }
__device__ __forceinline__ void pdl_trigger() { asm volatile("griddepcontrol.launch_dependents;" ::: "memory"); }
__device__ __forceinline__ void pdl_wait() { asm volatile("griddepcontrol.wait;" ::: "memory"); }
__device__ __forceinline__ void bar_sync(int id, int n) { asm volatile("bar.sync %0, %1;" ::"r"(id), "r"(n) : "memory"); }
__device__ __forceinline__ void wg_fence() { asm volatile("wgmma.fence.sync.aligned;" ::: "memory"); }
__device__ __forceinline__ void wg_commit() { asm volatile("wgmma.commit_group.sync.aligned;" ::: "memory"); }
template <int N> __device__ __forceinline__ void wg_wait() { asm volatile("wgmma.wait_group.sync.aligned %0;" ::"n"(N) : "memory"); }
__device__ __forceinline__ uint64_t mkdesc(uint32_t addr, uint32_t lbo, uint32_t sbo, uint32_t swz) {
  return (uint64_t)((addr & 0x3FFFF) >> 4) | ((uint64_t)(lbo >> 4) << 16) | ((uint64_t)(sbo >> 4) << 32) | ((uint64_t)swz << 62);
}
template <int N> __device__ __forceinline__ void fence_regs(float* d) {
#pragma unroll
  for (int i = 0; i < N; i++) asm volatile("" : "+f"(d[i])::"memory");
}
template <int N> __device__ __forceinline__ void fence_regs_u(uint32_t* d) {
#pragma unroll
  for (int i = 0; i < N; i++) asm volatile("" : "+r"(d[i])::"memory");
}
__device__ __forceinline__ uint32_t pack_bf16(float lo, float hi) {
  uint32_t r;
  asm("cvt.rn.bf16x2.f32 %0, %1, %2;" : "=r"(r) : "f"(hi), "f"(lo));
  return r;
}
__device__ __forceinline__ float bf_lo(uint32_t u) { return __uint_as_float(u << 16); }
__device__ __forceinline__ float bf_hi(uint32_t u) { return __uint_as_float(u & 0xFFFF0000u); }
__device__ __forceinline__ float ex2f(float x) {
  float y;
  asm("ex2.approx.ftz.f32 %0, %1;" : "=f"(y) : "f"(x));
  return y;
}
__device__ __forceinline__ void stsm4(uint32_t a, uint32_t r0, uint32_t r1, uint32_t r2, uint32_t r3) {
  asm volatile("stmatrix.sync.aligned.m8n8.x4.shared.b16 [%0], {%1,%2,%3,%4};" ::"r"(a), "r"(r0), "r"(r1), "r"(r2), "r"(r3) : "memory");
}
__device__ __forceinline__ void ldsm4(uint32_t* r, uint32_t a) {
  asm volatile("ldmatrix.sync.aligned.m8n8.x4.shared.b16 {%0,%1,%2,%3}, [%4];" : "=r"(r[0]), "=r"(r[1]), "=r"(r[2]), "=r"(r[3]) : "r"(a) : "memory");
}
__device__ __forceinline__ void ldsm4t(uint32_t* r, uint32_t a) {
  asm volatile("ldmatrix.sync.aligned.m8n8.x4.trans.shared.b16 {%0,%1,%2,%3}, [%4];" : "=r"(r[0]), "=r"(r[1]), "=r"(r[2]), "=r"(r[3]) : "r"(a) : "memory");
}
__device__ __forceinline__ void mma16816(float* d, const uint32_t* a, uint32_t b0, uint32_t b1) {
  asm volatile("mma.sync.aligned.m16n8k16.row.col.f32.bf16.bf16.f32 {%0,%1,%2,%3}, {%4,%5,%6,%7}, {%8,%9}, {%0,%1,%2,%3};"
               : "+f"(d[0]), "+f"(d[1]), "+f"(d[2]), "+f"(d[3]) : "r"(a[0]), "r"(a[1]), "r"(a[2]), "r"(a[3]), "r"(b0), "r"(b1));
}
__device__ __forceinline__ void row_stats(const float2* __restrict__ st, int row, float& mean, float& rstd) {
  const float4* p = reinterpret_cast<const float4*>(st + row * 8);
  float s = 0.f, q = 0.f;
#pragma unroll
  for (int i = 0; i < 4; i++) {
    float4 v = __ldcg(p + i);
    s += v.x + v.z;
    q += v.y + v.w;
  }
  mean = s * (1.f / D_);
  float var = fmaxf(q * (1.f / D_) - mean * mean, 0.f);
  rstd = rsqrtf(var + LN_EPS);
}

__device__ __forceinline__ void wgmma_rs_n64(float* d, uint32_t a0, uint32_t a1, uint32_t a2, uint32_t a3, uint64_t descB, int scaleD){
  asm volatile("{.reg .pred p; setp.ne.b32 p, %37, 0; wgmma.mma_async.sync.aligned.m64n64k16.f32.bf16.bf16 {%0,%1,%2,%3,%4,%5,%6,%7,%8,%9,%10,%11,%12,%13,%14,%15,%16,%17,%18,%19,%20,%21,%22,%23,%24,%25,%26,%27,%28,%29,%30,%31}, {%32,%33,%34,%35}, %36, p, 1, 1, 0;}"
   : "+f"(d[0]),"+f"(d[1]),"+f"(d[2]),"+f"(d[3]),"+f"(d[4]),"+f"(d[5]),"+f"(d[6]),"+f"(d[7]),"+f"(d[8]),"+f"(d[9]),"+f"(d[10]),"+f"(d[11]),"+f"(d[12]),"+f"(d[13]),"+f"(d[14]),"+f"(d[15]),"+f"(d[16]),"+f"(d[17]),"+f"(d[18]),"+f"(d[19]),"+f"(d[20]),"+f"(d[21]),"+f"(d[22]),"+f"(d[23]),"+f"(d[24]),"+f"(d[25]),"+f"(d[26]),"+f"(d[27]),"+f"(d[28]),"+f"(d[29]),"+f"(d[30]),"+f"(d[31])
   : "r"(a0),"r"(a1),"r"(a2),"r"(a3),"l"(descB),"r"(scaleD));
}

__device__ __forceinline__ void wgmma_rs_tb_n24(float* d, uint32_t a0, uint32_t a1, uint32_t a2, uint32_t a3, uint64_t descB, int scaleD){
  asm volatile("{.reg .pred p; setp.ne.b32 p, %17, 0; wgmma.mma_async.sync.aligned.m64n24k16.f32.bf16.bf16 {%0,%1,%2,%3,%4,%5,%6,%7,%8,%9,%10,%11}, {%12,%13,%14,%15}, %16, p, 1, 1, 1;}"
   : "+f"(d[0]),"+f"(d[1]),"+f"(d[2]),"+f"(d[3]),"+f"(d[4]),"+f"(d[5]),"+f"(d[6]),"+f"(d[7]),"+f"(d[8]),"+f"(d[9]),"+f"(d[10]),"+f"(d[11])
   : "r"(a0),"r"(a1),"r"(a2),"r"(a3),"l"(descB),"r"(scaleD));
}

__device__ __forceinline__ void wgmma_ss_tb_n128(float* d, uint64_t descA, uint64_t descB, int scaleD){
  asm volatile("{.reg .pred p; setp.ne.b32 p, %66, 0; wgmma.mma_async.sync.aligned.m64n128k16.f32.bf16.bf16 {%0,%1,%2,%3,%4,%5,%6,%7,%8,%9,%10,%11,%12,%13,%14,%15,%16,%17,%18,%19,%20,%21,%22,%23,%24,%25,%26,%27,%28,%29,%30,%31,%32,%33,%34,%35,%36,%37,%38,%39,%40,%41,%42,%43,%44,%45,%46,%47,%48,%49,%50,%51,%52,%53,%54,%55,%56,%57,%58,%59,%60,%61,%62,%63}, %64, %65, p, 1, 1, 0, 1;}"
   : "+f"(d[0]),"+f"(d[1]),"+f"(d[2]),"+f"(d[3]),"+f"(d[4]),"+f"(d[5]),"+f"(d[6]),"+f"(d[7]),"+f"(d[8]),"+f"(d[9]),"+f"(d[10]),"+f"(d[11]),"+f"(d[12]),"+f"(d[13]),"+f"(d[14]),"+f"(d[15]),"+f"(d[16]),"+f"(d[17]),"+f"(d[18]),"+f"(d[19]),"+f"(d[20]),"+f"(d[21]),"+f"(d[22]),"+f"(d[23]),"+f"(d[24]),"+f"(d[25]),"+f"(d[26]),"+f"(d[27]),"+f"(d[28]),"+f"(d[29]),"+f"(d[30]),"+f"(d[31]),"+f"(d[32]),"+f"(d[33]),"+f"(d[34]),"+f"(d[35]),"+f"(d[36]),"+f"(d[37]),"+f"(d[38]),"+f"(d[39]),"+f"(d[40]),"+f"(d[41]),"+f"(d[42]),"+f"(d[43]),"+f"(d[44]),"+f"(d[45]),"+f"(d[46]),"+f"(d[47]),"+f"(d[48]),"+f"(d[49]),"+f"(d[50]),"+f"(d[51]),"+f"(d[52]),"+f"(d[53]),"+f"(d[54]),"+f"(d[55]),"+f"(d[56]),"+f"(d[57]),"+f"(d[58]),"+f"(d[59]),"+f"(d[60]),"+f"(d[61]),"+f"(d[62]),"+f"(d[63])
   : "l"(descA),"l"(descB),"r"(scaleD));
}

__device__ __forceinline__ void wgmma_ss_tb_n136(float* d, uint64_t descA, uint64_t descB, int scaleD){
  asm volatile("{.reg .pred p; setp.ne.b32 p, %70, 0; wgmma.mma_async.sync.aligned.m64n136k16.f32.bf16.bf16 {%0,%1,%2,%3,%4,%5,%6,%7,%8,%9,%10,%11,%12,%13,%14,%15,%16,%17,%18,%19,%20,%21,%22,%23,%24,%25,%26,%27,%28,%29,%30,%31,%32,%33,%34,%35,%36,%37,%38,%39,%40,%41,%42,%43,%44,%45,%46,%47,%48,%49,%50,%51,%52,%53,%54,%55,%56,%57,%58,%59,%60,%61,%62,%63,%64,%65,%66,%67}, %68, %69, p, 1, 1, 0, 1;}"
   : "+f"(d[0]),"+f"(d[1]),"+f"(d[2]),"+f"(d[3]),"+f"(d[4]),"+f"(d[5]),"+f"(d[6]),"+f"(d[7]),"+f"(d[8]),"+f"(d[9]),"+f"(d[10]),"+f"(d[11]),"+f"(d[12]),"+f"(d[13]),"+f"(d[14]),"+f"(d[15]),"+f"(d[16]),"+f"(d[17]),"+f"(d[18]),"+f"(d[19]),"+f"(d[20]),"+f"(d[21]),"+f"(d[22]),"+f"(d[23]),"+f"(d[24]),"+f"(d[25]),"+f"(d[26]),"+f"(d[27]),"+f"(d[28]),"+f"(d[29]),"+f"(d[30]),"+f"(d[31]),"+f"(d[32]),"+f"(d[33]),"+f"(d[34]),"+f"(d[35]),"+f"(d[36]),"+f"(d[37]),"+f"(d[38]),"+f"(d[39]),"+f"(d[40]),"+f"(d[41]),"+f"(d[42]),"+f"(d[43]),"+f"(d[44]),"+f"(d[45]),"+f"(d[46]),"+f"(d[47]),"+f"(d[48]),"+f"(d[49]),"+f"(d[50]),"+f"(d[51]),"+f"(d[52]),"+f"(d[53]),"+f"(d[54]),"+f"(d[55]),"+f"(d[56]),"+f"(d[57]),"+f"(d[58]),"+f"(d[59]),"+f"(d[60]),"+f"(d[61]),"+f"(d[62]),"+f"(d[63]),"+f"(d[64]),"+f"(d[65]),"+f"(d[66]),"+f"(d[67])
   : "l"(descA),"l"(descB),"r"(scaleD));
}

__device__ __forceinline__ void wgmma_ss_tb_n224(float* d, uint64_t descA, uint64_t descB, int scaleD){
  asm volatile("{.reg .pred p; setp.ne.b32 p, %114, 0; wgmma.mma_async.sync.aligned.m64n224k16.f32.bf16.bf16 {%0,%1,%2,%3,%4,%5,%6,%7,%8,%9,%10,%11,%12,%13,%14,%15,%16,%17,%18,%19,%20,%21,%22,%23,%24,%25,%26,%27,%28,%29,%30,%31,%32,%33,%34,%35,%36,%37,%38,%39,%40,%41,%42,%43,%44,%45,%46,%47,%48,%49,%50,%51,%52,%53,%54,%55,%56,%57,%58,%59,%60,%61,%62,%63,%64,%65,%66,%67,%68,%69,%70,%71,%72,%73,%74,%75,%76,%77,%78,%79,%80,%81,%82,%83,%84,%85,%86,%87,%88,%89,%90,%91,%92,%93,%94,%95,%96,%97,%98,%99,%100,%101,%102,%103,%104,%105,%106,%107,%108,%109,%110,%111}, %112, %113, p, 1, 1, 0, 1;}"
   : "+f"(d[0]),"+f"(d[1]),"+f"(d[2]),"+f"(d[3]),"+f"(d[4]),"+f"(d[5]),"+f"(d[6]),"+f"(d[7]),"+f"(d[8]),"+f"(d[9]),"+f"(d[10]),"+f"(d[11]),"+f"(d[12]),"+f"(d[13]),"+f"(d[14]),"+f"(d[15]),"+f"(d[16]),"+f"(d[17]),"+f"(d[18]),"+f"(d[19]),"+f"(d[20]),"+f"(d[21]),"+f"(d[22]),"+f"(d[23]),"+f"(d[24]),"+f"(d[25]),"+f"(d[26]),"+f"(d[27]),"+f"(d[28]),"+f"(d[29]),"+f"(d[30]),"+f"(d[31]),"+f"(d[32]),"+f"(d[33]),"+f"(d[34]),"+f"(d[35]),"+f"(d[36]),"+f"(d[37]),"+f"(d[38]),"+f"(d[39]),"+f"(d[40]),"+f"(d[41]),"+f"(d[42]),"+f"(d[43]),"+f"(d[44]),"+f"(d[45]),"+f"(d[46]),"+f"(d[47]),"+f"(d[48]),"+f"(d[49]),"+f"(d[50]),"+f"(d[51]),"+f"(d[52]),"+f"(d[53]),"+f"(d[54]),"+f"(d[55]),"+f"(d[56]),"+f"(d[57]),"+f"(d[58]),"+f"(d[59]),"+f"(d[60]),"+f"(d[61]),"+f"(d[62]),"+f"(d[63]),"+f"(d[64]),"+f"(d[65]),"+f"(d[66]),"+f"(d[67]),"+f"(d[68]),"+f"(d[69]),"+f"(d[70]),"+f"(d[71]),"+f"(d[72]),"+f"(d[73]),"+f"(d[74]),"+f"(d[75]),"+f"(d[76]),"+f"(d[77]),"+f"(d[78]),"+f"(d[79]),"+f"(d[80]),"+f"(d[81]),"+f"(d[82]),"+f"(d[83]),"+f"(d[84]),"+f"(d[85]),"+f"(d[86]),"+f"(d[87]),"+f"(d[88]),"+f"(d[89]),"+f"(d[90]),"+f"(d[91]),"+f"(d[92]),"+f"(d[93]),"+f"(d[94]),"+f"(d[95]),"+f"(d[96]),"+f"(d[97]),"+f"(d[98]),"+f"(d[99]),"+f"(d[100]),"+f"(d[101]),"+f"(d[102]),"+f"(d[103]),"+f"(d[104]),"+f"(d[105]),"+f"(d[106]),"+f"(d[107]),"+f"(d[108]),"+f"(d[109]),"+f"(d[110]),"+f"(d[111])
   : "l"(descA),"l"(descB),"r"(scaleD));
}

constexpr int QKV_BCH = 17408;
constexpr int QKV_A = 0, QKV_B = 65536, QKV_AUX = QKV_B + 8 * QKV_BCH;
constexpr int QKV_SMEM = QKV_AUX + 2048 + 1024;

__device__ __forceinline__ void cp_async_wait_chunk(int kc) {
  switch (kc) {
    case 0: asm volatile("cp.async.wait_group 7;" ::: "memory"); break;
    case 1: asm volatile("cp.async.wait_group 6;" ::: "memory"); break;
    case 2: asm volatile("cp.async.wait_group 5;" ::: "memory"); break;
    case 3: asm volatile("cp.async.wait_group 4;" ::: "memory"); break;
    case 4: asm volatile("cp.async.wait_group 3;" ::: "memory"); break;
    case 5: asm volatile("cp.async.wait_group 2;" ::: "memory"); break;
    case 6: asm volatile("cp.async.wait_group 1;" ::: "memory"); break;
    default: asm volatile("cp.async.wait_group 0;" ::: "memory"); break;
  }
}

template <bool FIRST>
__global__ void __launch_bounds__(256, 1) qkv_kernel(const bf16* __restrict__ x, const bf16* __restrict__ wq, const bf16* __restrict__ wk,
                                                      const bf16* __restrict__ wv) {
  extern __shared__ uint8_t smraw[];
  const uint32_t sb = (smem_u32(smraw) + 1023) & ~1023u;
  uint8_t* sp = smraw + (sb - smem_u32(smraw));
  float* s_mean = reinterpret_cast<float*>(sp + QKV_AUX);
  float* s_rstd = s_mean + 64;
  float* s_cs = s_rstd + 64;
  float* s_km = s_cs + 136;
  const uint32_t bars = sb + QKV_AUX + 1536;
  const int tid = threadIdx.x, lane = tid & 31, warp = tid >> 5;
  const int tb = blockIdx.x >> 2, hg = blockIdx.x & 3;
  const int KID = FIRST ? 1 : 6;
  if (tid == 0) TS(KID, 0);
  if (FIRST && tid == 0 && blockIdx.x == 0) GT(0);
  pdl_trigger();
  if (FIRST) {
    const bf16* wkv = (hg < 2 ? wk : wv) + (hg & 1) * 8;
#pragma unroll 1
    for (int kc = 0; kc < 8; kc++) {
#pragma unroll
      for (int i = 0; i < 2; i++) {
        const int ch = i * 256 + tid, row = ch >> 3, c = ch & 7;
        cp_async16(sb + QKV_A + kc * 8192 + row * 128 + ((c ^ (row & 7)) << 4), x + (size_t)(tb * 64 + row) * D_ + kc * 64 + c * 8);
      }
#pragma unroll
      for (int i = 0; i < 4; i++) {
        const int u = i * 8 + warp, kg = u >> 2, nb = (u & 3) * 4 + (lane >> 3), k = kg * 8 + (lane & 7);
        cp_async16(sb + QKV_B + kc * QKV_BCH + kg * 2176 + nb * 128 + (lane & 7) * 16, wq + (size_t)(kc * 64 + k) * D_ + hg * 128 + nb * 8);
      }
      if (tid < 64) cp_async16(sb + QKV_B + kc * QKV_BCH + (tid >> 3) * 2176 + 2048 + (tid & 7) * 16, wkv + (size_t)(kc * 64 + tid) * 16);
      asm volatile("cp.async.commit_group;" ::: "memory");
    }
  } else {
    if (tid == 0) {
      for (int i = 0; i < 8; i++) mbar_init(bars + i * 8, 1);
      mbar_fence_init();
    }
    __syncthreads();
    if (lane == 0) {
      mbar_expect(bars + warp * 8, 8192 + QKV_BCH);
      bulk_g2s(sb + QKV_B + warp * QKV_BCH, g_Wqkvp + (hg * 8 + warp) * QKV_BCH, QKV_BCH, bars + warp * 8);
      if (tid == 0) TS(KID, 6);
      pdl_wait();
      if (tid == 0) TS(KID, 5);
      bulk_g2s(sb + QKV_A + warp * 8192, g_x2T + (tb * 8 + warp) * 8192, 8192, bars + warp * 8);
    }
    __syncwarp();
  }
  if (warp >= 4) {
    const int t1 = tid & 127;
    if (!FIRST) {
      pdl_wait();
      if (t1 < 64) {
        float mean, rstd;
        row_stats(g_statA, tb * 64 + t1, mean, rstd);
        s_mean[t1] = mean; s_rstd[t1] = rstd;
      }
      s_cs[t1] = __ldcg(g_csQKV + hg * 136 + t1);
      if (t1 < 8) s_cs[128 + t1] = __ldcg(g_csQKV + hg * 136 + 128 + t1);
    } else {
      float cs[8], ckv[8], rs = 0.f, rq = 0.f;
#pragma unroll
      for (int i = 0; i < 8; i++) cs[i] = ckv[i] = 0.f;
#pragma unroll 1
      for (int kc = 0; kc < 8; kc++) {
        cp_async_wait_chunk(kc);
        fence_async_smem();
        bar_sync(4, 256);
        const uint8_t* bch = sp + QKV_B + kc * QKV_BCH;
#pragma unroll
        for (int kg = 0; kg < 8; kg++) {
          const uint4 v = *reinterpret_cast<const uint4*>(bch + kg * 2176 + t1 * 16);
          cs[0] += bf_lo(v.x); cs[1] += bf_hi(v.x); cs[2] += bf_lo(v.y); cs[3] += bf_hi(v.y);
          cs[4] += bf_lo(v.z); cs[5] += bf_hi(v.z); cs[6] += bf_lo(v.w); cs[7] += bf_hi(v.w);
        }
        if (t1 < 64) {
          const uint4 v = *reinterpret_cast<const uint4*>(bch + (t1 >> 3) * 2176 + 2048 + (t1 & 7) * 16);
          ckv[0] += bf_lo(v.x); ckv[1] += bf_hi(v.x); ckv[2] += bf_lo(v.y); ckv[3] += bf_hi(v.y);
          ckv[4] += bf_lo(v.z); ckv[5] += bf_hi(v.z); ckv[6] += bf_lo(v.w); ckv[7] += bf_hi(v.w);
        }
        const int row = t1 >> 1;
#pragma unroll
        for (int j = 0; j < 4; j++) {
          const uint4 v = *reinterpret_cast<const uint4*>(sp + QKV_A + kc * 8192 + row * 128 + (((j + 4 * (t1 & 1) + row) & 7) << 4));
          const float f[8] = {bf_lo(v.x), bf_hi(v.x), bf_lo(v.y), bf_hi(v.y), bf_lo(v.z), bf_hi(v.z), bf_lo(v.w), bf_hi(v.w)};
#pragma unroll
          for (int i = 0; i < 8; i++) { rs += f[i]; rq += f[i] * f[i]; }
        }
      }
      rs += __shfl_xor_sync(~0u, rs, 1); rq += __shfl_xor_sync(~0u, rq, 1);
      const float mean = rs * (1.f / D_);
      if ((t1 & 1) == 0) { s_mean[t1 >> 1] = mean; s_rstd[t1 >> 1] = rsqrtf(fmaxf(rq * (1.f / D_) - mean * mean, 0.f) + LN_EPS); }
#pragma unroll
      for (int i = 0; i < 8; i++) {
#pragma unroll
        for (int o = 1; o < 8; o <<= 1) { cs[i] += __shfl_xor_sync(~0u, cs[i], o); ckv[i] += __shfl_xor_sync(~0u, ckv[i], o); }
      }
      float* s_tmp = s_km + 32;
      if ((t1 & 7) == 0) {
#pragma unroll
        for (int i = 0; i < 8; i++) { s_cs[(t1 >> 3) * 8 + i] = cs[i]; if (t1 < 64) s_tmp[(t1 >> 3) * 8 + i] = ckv[i]; }
      }
      bar_sync(2, 128);
      if (t1 < 8) {
        float s = 0.f;
#pragma unroll
        for (int gq = 0; gq < 8; gq++) s += s_tmp[gq * 8 + t1];
        s_cs[128 + t1] = s;
      }
      bar_sync(2, 128);
      if (tb == 0) {
        for (int i = t1; i < 136; i += 128) g_csQKV[hg * 136 + i] = s_cs[i];
        if (t1 == 0) bulk_s2g(g_Wqkvp + hg * 8 * QKV_BCH, sb + QKV_B, 8 * QKV_BCH);
      }
      if (hg == 0 && t1 == 0) bulk_s2g(g_x0T + tb * 65536, sb + QKV_A, 65536);
      if (t1 == 0) asm volatile("cp.async.bulk.commit_group;" ::: "memory");
    }
    asm volatile("bar.arrive 1, 256;" ::: "memory");
    if (FIRST && t1 == 0) asm volatile("cp.async.bulk.wait_group 0;" ::: "memory");
    return;
  }
  float acc[68];
#pragma unroll
  for (int i = 0; i < 68; i++) acc[i] = 0.f;
  fence_regs<68>(acc);
#pragma unroll 1
  for (int kc = 0; kc < 8; kc++) {
    if (FIRST) {
      cp_async_wait_chunk(kc);
      fence_async_smem();
      bar_sync(4, 256);
    } else {
      mbar_wait(bars + kc * 8, 0);
    }
    if (tid == 0 && kc == 0) TS(KID, 1);
    wg_fence();
#pragma unroll
    for (int ks = 0; ks < 4; ks++)
      wgmma_ss_tb_n136(acc, mkdesc(sb + QKV_A + kc * 8192 + ks * 32, 16, 1024, 1),
                       mkdesc(sb + QKV_B + kc * QKV_BCH + ks * 2 * 2176, 2176, 128, 0), 1);
    wg_commit();
  }
  wg_wait<0>();
  fence_regs<68>(acc);
  if (tid == 0) TS(KID, 2);
  bar_sync(1, 256);
  if (!FIRST) pdl_wait();
  if (tid == 0) TS(KID, 4);
  const int g = lane >> 2, t = lane & 3;
  const int rl0 = warp * 16 + g, r0 = tb * 64 + rl0;
  const float mean0 = s_mean[rl0], rstd0 = s_rstd[rl0], mean1 = s_mean[rl0 + 8], rstd1 = s_rstd[rl0 + 8];
  {
    const float q0 = rstd0 * QSCALE, q1 = rstd1 * QSCALE;
    uint32_t* qp0 = reinterpret_cast<uint32_t*>(g_Q + (size_t)r0 * D_ + hg * 128) + t;
    uint32_t* qp1 = qp0 + 8 * (D_ / 2);
#pragma unroll
    for (int j = 0; j < 16; j++) {
      const float2 c = *reinterpret_cast<const float2*>(s_cs + 8 * j + 2 * t);
      const float* a = acc + 4 * j;
      qp0[4 * j] = pack_bf16((a[0] - mean0 * c.x) * q0, (a[1] - mean0 * c.y) * q0);
      qp1[4 * j] = pack_bf16((a[2] - mean1 * c.x) * q1, (a[3] - mean1 * c.y) * q1);
    }
  }
  {
    const float2 c = *reinterpret_cast<const float2*>(s_cs + 128 + 2 * t);
    uint32_t u0 = pack_bf16((acc[64] - mean0 * c.x) * rstd0, (acc[65] - mean0 * c.y) * rstd0);
    uint32_t u1 = pack_bf16((acc[66] - mean1 * c.x) * rstd1, (acc[67] - mean1 * c.y) * rstd1);
    uint8_t* kv = g_KV + (r0 >> 8) * 16384;
    const int kk = r0 & 255;
    if (hg < 2) {
      *reinterpret_cast<uint32_t*>(kv + (kk >> 3) * 256 + hg * 128 + (kk & 7) * 16 + t * 4) = u0;
      *reinterpret_cast<uint32_t*>(kv + ((kk + 8) >> 3) * 256 + hg * 128 + (kk & 7) * 16 + t * 4) = u1;
      float m0 = fmaxf(fabsf(bf_lo(u0)), fabsf(bf_lo(u1))), m1 = fmaxf(fabsf(bf_hi(u0)), fabsf(bf_hi(u1)));
      if (!(bf_lo(u0) == bf_lo(u0)) || !(bf_lo(u1) == bf_lo(u1))) m0 = __int_as_float(0x7f800000);
      if (!(bf_hi(u0) == bf_hi(u0)) || !(bf_hi(u1) == bf_hi(u1))) m1 = __int_as_float(0x7f800000);
#pragma unroll
      for (int o = 4; o < 32; o <<= 1) { m0 = fmaxf(m0, __shfl_xor_sync(~0u, m0, o)); m1 = fmaxf(m1, __shfl_xor_sync(~0u, m1, o)); }
      if (g == 0) { s_km[warp * 8 + 2 * t] = m0; s_km[warp * 8 + 2 * t + 1] = m1; }
      bar_sync(3, 128);
      if (tid < 8) g_kmax[tb * 16 + hg * 8 + tid] = fmaxf(fmaxf(s_km[tid], s_km[8 + tid]), fmaxf(s_km[16 + tid], s_km[24 + tid]));
    } else {
      const uint32_t mask = ((r0 >> 6) & 1) ? LUT_MASK_ODD : LUT_MASK_EVEN;
      if ((mask >> ((r0 >> 3) & 7)) & 1) u0 ^= 0x80008000u;
      if ((mask >> (((r0 + 8) >> 3) & 7)) & 1) u1 ^= 0x80008000u;
      *reinterpret_cast<uint32_t*>(kv + 8192 + (hg - 2) * 4096 + kk * 16 + t * 4) = u0;
      *reinterpret_cast<uint32_t*>(kv + 8192 + (hg - 2) * 4096 + (kk + 8) * 16 + t * 4) = u1;
    }
  }
  if (tid == 0) TS(KID, 3);
}

constexpr int ATT_SMEM = 31 * 1024 + 192 * 1024 + 2048 + 1024;
constexpr int KVCH = 20480;
constexpr float LUT_MAGIC = 382.875f;

template <uint32_t MASK>
__device__ __forceinline__ void exp_pack(const float* s, uint32_t* p, uint32_t lutlane) {
#pragma unroll
  for (int i = 0; i < 16; i++) {
    if ((MASK >> (i / 2)) & 1) {
      const uint32_t b0 = __float_as_uint(s[2 * i] + LUT_MAGIC), b1 = __float_as_uint(s[2 * i + 1] + LUT_MAGIC);
      uint32_t c0, c1, w;
      asm volatile("ld.shared.u16 %0, [%1+2];" : "=r"(c0) : "r"((b0 & 0x7F80u) | lutlane));
      asm volatile("ld.shared.u32 %0, [%1];" : "=r"(c1) : "r"((b1 & 0x7F80u) | lutlane));
      asm("prmt.b32 %0, %1, %2, 0x6521;" : "=r"(w) : "r"(b0), "r"(b1));
      p[i] = w + c0 + c1;
    } else {
      p[i] = pack_bf16(ex2f(s[2 * i]), ex2f(s[2 * i + 1]));
    }
  }
}

__device__ __noinline__ void pack_weights(const bf16* __restrict__ wo, const bf16* __restrict__ w1, const bf16* __restrict__ w2, int cta) {
  const int lane = threadIdx.x & 31, w = cta * 16 + (threadIdx.x >> 5);
  const int kr = lane & 7, ng = lane >> 3;
  constexpr int U = 16;
  if (w < 56) {
    {
      const int nbg = 4 * w + ng, fs = nbg / 28, nb = nbg % 28;
      float cs[8];
#pragma unroll
      for (int i = 0; i < 8; i++) cs[i] = 0.f;
#pragma unroll 1
      for (int k0 = 0; k0 < 64; k0 += U) {
        uint4 v[U];
#pragma unroll
        for (int u = 0; u < U; u++) v[u] = __ldg(reinterpret_cast<const uint4*>(w1 + (size_t)((k0 + u) * 8 + kr) * F_ + nbg * 8));
#pragma unroll
        for (int u = 0; u < U; u++) {
          const int kg = k0 + u;
          *reinterpret_cast<uint4*>(g_W1p + (fs * 8 + (kg >> 3)) * 28672 + (kg & 7) * 3584 + nb * 128 + kr * 16) = v[u];
          cs[0] += bf_lo(v[u].x); cs[1] += bf_hi(v[u].x); cs[2] += bf_lo(v[u].y); cs[3] += bf_hi(v[u].y);
          cs[4] += bf_lo(v[u].z); cs[5] += bf_hi(v[u].z); cs[6] += bf_lo(v[u].w); cs[7] += bf_hi(v[u].w);
        }
      }
#pragma unroll
      for (int i = 0; i < 8; i++) {
#pragma unroll
        for (int o = 1; o < 8; o <<= 1) cs[i] += __shfl_xor_sync(~0u, cs[i], o);
      }
      if (kr == 0) {
#pragma unroll
        for (int i = 0; i < 8; i++) g_cs1[nbg * 8 + i] = cs[i];
      }
    }
#pragma unroll 1
    for (int i0 = 64 * w; i0 < 64 * w + 64; i0 += U) {
      uint4 v[U];
#pragma unroll
      for (int u = 0; u < U; u++) {
        const int it = i0 + u, kg = it >> 4, nbg = (it & 15) * 4 + ng;
        v[u] = __ldg(reinterpret_cast<const uint4*>(w2 + (size_t)(kg * 8 + kr) * D_ + nbg * 8));
      }
#pragma unroll
      for (int u = 0; u < U; u++) {
        const int it = i0 + u, kg = it >> 4, nbg = (it & 15) * 4 + ng;
        *reinterpret_cast<uint4*>(g_W2p + ((nbg >> 4) * 28 + (kg >> 3)) * 16384 + (kg & 7) * 2048 + (nbg & 15) * 128 + kr * 16) = v[u];
      }
    }
  } else {
#pragma unroll 1
    for (int i0 = 128 * (w - 56); i0 < 128 * (w - 56) + 128; i0 += U) {
      uint4 v[U];
#pragma unroll
      for (int u = 0; u < U; u++) {
        const int it = i0 + u, kg = it >> 4, nbg = (it & 15) * 4 + ng;
        v[u] = __ldg(reinterpret_cast<const uint4*>(wo + (size_t)(kg * 8 + kr) * D_ + nbg * 8));
      }
#pragma unroll
      for (int u = 0; u < U; u++) {
        const int it = i0 + u, kg = it >> 4, nbg = (it & 15) * 4 + ng;
        *reinterpret_cast<uint4*>(g_Wop + ((nbg >> 4) * 8 + (kg >> 3)) * 16384 + (kg & 7) * 2048 + (nbg & 15) * 128 + kr * 16) = v[u];
      }
    }
  }
  __threadfence();
  __syncthreads();
  if (threadIdx.x == 0) asm volatile("red.release.gpu.global.add.u32 [%0], 1;" ::"l"(&g_pack_done) : "memory");
}

__global__ void __launch_bounds__(512, 1) attn_kernel(const bf16* __restrict__ wo, const bf16* __restrict__ w1, const bf16* __restrict__ w2, int KID) {
  extern __shared__ uint8_t smraw[];
  const uint32_t sbase = smem_u32(smraw);
  const uint32_t bars = sbase;
  const uint32_t kred = sbase + 128;
  const uint32_t LUT = (sbase + 2048 + 16384 + 32767) & ~32767u;
  const uint32_t KS = LUT + 32768;
  uint8_t* sm0 = smraw - sbase;
  const int tid = threadIdx.x, lane = tid & 31, wg = tid >> 7, warp = (tid >> 5) & 3;
  if (blockIdx.x >= 128) { pdl_trigger(); pack_weights(wo, w1, w2, blockIdx.x - 128); return; }
  if (tid == 0) TS(KID, 0);
  pdl_trigger();
  if (tid == 0) {
    for (int i = 0; i < 8; i++) mbar_init(bars + i * 8, 1);
    mbar_fence_init();
  }
  for (int i = tid; i < 256 * 32; i += 512) {
    const int idx = i >> 5;
    const float v = exp2f((idx + 0.5f) * (1.f / 256.f) + 0.125f);
    const int target = (v < 2.f) ? (int)rintf(128.f * v) - 128 : (int)rintf(64.f * v);
    reinterpret_cast<uint32_t*>(sm0 + LUT)[i] = (uint32_t)(target - (idx >> 1)) << 16;
  }
  for (int i = tid; i < S_; i += 512) {
    const uint32_t mask = ((i >> 6) & 1) ? LUT_MASK_ODD : LUT_MASK_EVEN;
    const uint32_t o = ((mask >> ((i >> 3) & 7)) & 1) ? 0xBF80BF80u : 0x3F803F80u;
    *reinterpret_cast<uint4*>(sm0 + KS + (i >> 8) * KVCH + 16384 + (i & 255) * 16) = make_uint4(o, o, o, o);
  }
  fence_async_smem();
  __syncthreads();
  if (tid == 0) TS(KID, 5);
  pdl_wait();
  if (tid == 0) TS(KID, 4);
  if ((tid & 255) == 128) {
#pragma unroll 1
    for (int c = tid >> 8; c < 8; c += 2) {
      mbar_expect(bars + c * 8, 16384);
      bulk_g2s(KS + c * KVCH, g_KV + c * 16384, 16384, bars + c * 8);
    }
  }
  {
    float m = __ldcg(g_kmax + tid);
    m = fmaxf(m, __shfl_xor_sync(~0u, m, 16));
    if (lane < 16) reinterpret_cast<float*>(sm0 + kred)[(tid >> 5) * 16 + lane] = m;
  }
  const int g = lane >> 2, t = lane & 3;
  uint32_t qq[2][4];
#pragma unroll
  for (int tile = 0; tile < 2; tile++) {
    const int row0 = (blockIdx.x * 8 + wg * 2 + tile) * 64 + warp * 16 + g;
    const uint32_t* qp = reinterpret_cast<const uint32_t*>(g_Q);
    qq[tile][0] = __ldcg(qp + (size_t)row0 * 8 + t);
    qq[tile][1] = __ldcg(qp + (size_t)(row0 + 8) * 8 + t);
    qq[tile][2] = __ldcg(qp + (size_t)row0 * 8 + 4 + t);
    qq[tile][3] = __ldcg(qp + (size_t)(row0 + 8) * 8 + 4 + t);
  }
  __syncthreads();
  float km[4];
  {
    const float* kr = reinterpret_cast<const float*>(sm0 + kred);
    km[0] = km[1] = km[2] = km[3] = 0.f;
#pragma unroll
    for (int w = 0; w < 16; w++) {
      km[0] = fmaxf(km[0], kr[w * 16 + 2 * t]); km[1] = fmaxf(km[1], kr[w * 16 + 2 * t + 1]);
      km[2] = fmaxf(km[2], kr[w * 16 + 2 * t + 8]); km[3] = fmaxf(km[3], kr[w * 16 + 2 * t + 9]);
    }
  }
  uint32_t unsafe_bits = 0;
#pragma unroll
  for (int tile = 0; tile < 2; tile++) {
    const uint32_t* q = qq[tile];
    float b0 = fabsf(bf_lo(q[0])) * km[0] + fabsf(bf_hi(q[0])) * km[1] + fabsf(bf_lo(q[2])) * km[2] + fabsf(bf_hi(q[2])) * km[3];
    float b1 = fabsf(bf_lo(q[1])) * km[0] + fabsf(bf_hi(q[1])) * km[1] + fabsf(bf_lo(q[3])) * km[2] + fabsf(bf_hi(q[3])) * km[3];
    b0 += __shfl_xor_sync(~0u, b0, 1); b0 += __shfl_xor_sync(~0u, b0, 2);
    b1 += __shfl_xor_sync(~0u, b1, 1); b1 += __shfl_xor_sync(~0u, b1, 2);
    const uint32_t bad = !(b0 <= SAFE_SCORE_BOUND && b1 <= SAFE_SCORE_BOUND);
    uint32_t u;
    asm volatile("{.reg .pred p, r; setp.ne.u32 p, %1, 0; bar.red.or.pred r, %2, 128, p; selp.u32 %0, 1, 0, r;}"
                 : "=r"(u) : "r"(bad), "r"(1 + wg) : "memory");
    unsafe_bits |= (__any_sync(~0u, u) ? 1u : 0u) << tile;
    asm volatile("st.shared.v4.u32 [%0], {%1,%2,%3,%4};" ::"r"(sbase + 2048 + tile * 8192 + tid * 16), "r"(q[0]), "r"(q[1]), "r"(q[2]), "r"(q[3]) : "memory");
  }
  const uint32_t lutlane = LUT | (lane * 4);
  constexpr uint64_t KSTEP = (64 * 32) >> 4, VSTEP = (16 * 16) >> 4;
  constexpr uint64_t KJUMP = (KVCH - 3 * 2048) >> 4, VJUMP = (KVCH - 4096) >> 4;
#pragma unroll 1
  for (int tile = 0; tile < 2; tile++) {
    uint32_t q[4];
    asm volatile("ld.shared.v4.u32 {%0,%1,%2,%3}, [%4];" : "=r"(q[0]), "=r"(q[1]), "=r"(q[2]), "=r"(q[3]) : "r"(sbase + 2048 + tile * 8192 + tid * 16) : "memory");
    const uint32_t unsafe = (unsafe_bits >> tile) & 1;
    float o[12];
#pragma unroll
    for (int i = 0; i < 12; i++) o[i] = 0.f;
    uint64_t kd = mkdesc(KS, 128, 256, 0);
    uint64_t vd = mkdesc(KS + 8192, 128, 4096, 0);
    if (!unsafe) {
      float s[32];
      uint32_t p[16];
      mbar_wait(bars, 0);
      if (tid == 0 && tile == 0) TS(KID, 1);
      fence_regs<12>(o);
      wg_fence();
      wgmma_rs_n64(s, q[0], q[1], q[2], q[3], kd, 0); kd += KSTEP;
      wg_commit();
#pragma unroll 1
      for (int c = 0; c < 8; c++) {
        if (c < 7) mbar_wait(bars + (c + 1) * 8, 0);
#pragma unroll 1
        for (int j = 0; j < 2; j++) {
          wg_wait<0>(); fence_regs<32>(s); fence_regs<12>(o); fence_regs_u<16>(p);
          exp_pack<LUT_MASK_EVEN>(s, p, lutlane);
          wg_fence();
#pragma unroll
          for (int k = 0; k < 4; k++) { wgmma_rs_tb_n24(o, p[4 * k], p[4 * k + 1], p[4 * k + 2], p[4 * k + 3], vd, 1); vd += VSTEP; }
          wgmma_rs_n64(s, q[0], q[1], q[2], q[3], kd, 0); kd += j ? KJUMP : KSTEP;
          wg_commit();
          wg_wait<0>(); fence_regs<32>(s); fence_regs<12>(o); fence_regs_u<16>(p);
          exp_pack<LUT_MASK_ODD>(s, p, lutlane);
          wg_fence();
#pragma unroll
          for (int k = 0; k < 4; k++) { wgmma_rs_tb_n24(o, p[4 * k], p[4 * k + 1], p[4 * k + 2], p[4 * k + 3], vd, 1); vd += VSTEP; }
          wgmma_rs_n64(s, q[0], q[1], q[2], q[3], kd, 0); kd += KSTEP;
          wg_commit();
        }
        vd += VJUMP;
      }
      wg_wait<0>(); fence_regs<12>(o); fence_regs<32>(s);
    } else {
      for (int c = 0; c < 8; c++) mbar_wait(bars + c * 8, 0);
      float m0 = -INFINITY, m1 = -INFINITY;
#pragma unroll 1
      for (int kb = 0; kb < S_ / 16; kb++) {
        uint32_t kf[4];
        float sa[4] = {0.f, 0.f, 0.f, 0.f}, sc[4] = {0.f, 0.f, 0.f, 0.f};
        ldsm4(kf, KS + (kb >> 4) * KVCH + (kb & 15) * 512 + lane * 16);
        mma16816(sa, q, kf[0], kf[1]);
        mma16816(sc, q, kf[2], kf[3]);
        m0 = fmaxf(fmaxf(m0, fmaxf(sa[0], sa[1])), fmaxf(sc[0], sc[1]));
        m1 = fmaxf(fmaxf(m1, fmaxf(sa[2], sa[3])), fmaxf(sc[2], sc[3]));
      }
      m0 = fmaxf(m0, __shfl_xor_sync(~0u, m0, 1)); m0 = fmaxf(m0, __shfl_xor_sync(~0u, m0, 2));
      m1 = fmaxf(m1, __shfl_xor_sync(~0u, m1, 1)); m1 = fmaxf(m1, __shfl_xor_sync(~0u, m1, 2));
#pragma unroll 1
      for (int kb = 0; kb < S_ / 16; kb++) {
        uint32_t kf[4], vf[4], ef[4], a[4];
        float sa[4] = {0.f, 0.f, 0.f, 0.f}, sc[4] = {0.f, 0.f, 0.f, 0.f};
        const uint32_t chb = KS + (kb >> 4) * KVCH;
        ldsm4(kf, chb + (kb & 15) * 512 + lane * 16);
        const uint32_t krow = chb + 8192 + ((kb & 15) * 16 + (lane & 15)) * 16;
        ldsm4t(vf, krow + (lane >> 4) * 4096);
        ldsm4t(ef, krow + 8192);
        mma16816(sa, q, kf[0], kf[1]);
        mma16816(sc, q, kf[2], kf[3]);
        const uint32_t mask = ((kb >> 2) & 1) ? LUT_MASK_ODD : LUT_MASK_EVEN;
        const uint32_t sg0 = ((mask >> ((2 * kb) & 7)) & 1) ? 0x80008000u : 0u, sg1 = ((mask >> ((2 * kb + 1) & 7)) & 1) ? 0x80008000u : 0u;
        a[0] = pack_bf16(ex2f(sa[0] - m0), ex2f(sa[1] - m0)) ^ sg0;
        a[1] = pack_bf16(ex2f(sa[2] - m1), ex2f(sa[3] - m1)) ^ sg0;
        a[2] = pack_bf16(ex2f(sc[0] - m0), ex2f(sc[1] - m0)) ^ sg1;
        a[3] = pack_bf16(ex2f(sc[2] - m1), ex2f(sc[3] - m1)) ^ sg1;
        mma16816(o, a, vf[0], vf[1]);
        mma16816(o + 4, a, vf[2], vf[3]);
        mma16816(o + 8, a, ef[0], ef[1]);
      }
    }
    const float r0 = 1.f / o[8], r1 = 1.f / o[10];
    const int row0 = (blockIdx.x * 8 + wg * 2 + tile) * 64 + warp * 16 + g;
    const int tok = row0 >> 5, h0 = row0 & 31, h1 = h0 + 8, tr = tok & 63;
    uint8_t* ob = g_OT + (tok >> 6) * 65536 + tr * 128 + t * 4;
    uint8_t* o0 = ob + (h0 >> 2) * 8192;
    uint8_t* o1 = ob + (h1 >> 2) * 8192;
    const int c0 = (h0 & 3) * 2, sw = tr & 7;
    *reinterpret_cast<uint32_t*>(o0 + ((c0 ^ sw) << 4)) = pack_bf16(o[0] * r0, o[1] * r0);
    *reinterpret_cast<uint32_t*>(o1 + ((c0 ^ sw) << 4)) = pack_bf16(o[2] * r1, o[3] * r1);
    *reinterpret_cast<uint32_t*>(o0 + (((c0 + 1) ^ sw) << 4)) = pack_bf16(o[4] * r0, o[5] * r0);
    *reinterpret_cast<uint32_t*>(o1 + (((c0 + 1) ^ sw) << 4)) = pack_bf16(o[6] * r1, o[7] * r1);
    if (tid == 0 && tile == 0) TS(KID, 2);
  }
  if (tid == 0) TS(KID, 3);
}

__device__ __forceinline__ void residual_block(const float* a, uint32_t tile, int warp, int lane, float2* stat_out  ) {
  const int rl = warp * 16 + ((lane >> 3) & 1) * 8 + (lane & 7);
  const uint32_t rowa = tile + rl * 128;
  float s0 = 0.f, q0 = 0.f, s1 = 0.f, q1 = 0.f;
#pragma unroll
  for (int j = 0; j < 8; j += 2) {
    const uint32_t ad = rowa + (((j + (lane >> 4)) ^ (rl & 7)) << 4);
    uint32_t r[4];
    ldsm4(r, ad);
    const float* c = a + 4 * j;
    const uint32_t u0 = pack_bf16(bf_lo(r[0]) + c[0], bf_hi(r[0]) + c[1]);
    const uint32_t u1 = pack_bf16(bf_lo(r[1]) + c[2], bf_hi(r[1]) + c[3]);
    const uint32_t u2 = pack_bf16(bf_lo(r[2]) + c[4], bf_hi(r[2]) + c[5]);
    const uint32_t u3 = pack_bf16(bf_lo(r[3]) + c[6], bf_hi(r[3]) + c[7]);
    s0 += (bf_lo(u0) + bf_hi(u0)) + (bf_lo(u2) + bf_hi(u2));
    q0 += bf_lo(u0) * bf_lo(u0) + bf_hi(u0) * bf_hi(u0) + bf_lo(u2) * bf_lo(u2) + bf_hi(u2) * bf_hi(u2);
    s1 += (bf_lo(u1) + bf_hi(u1)) + (bf_lo(u3) + bf_hi(u3));
    q1 += bf_lo(u1) * bf_lo(u1) + bf_hi(u1) * bf_hi(u1) + bf_lo(u3) * bf_lo(u3) + bf_hi(u3) * bf_hi(u3);
    stsm4(ad, u0, u1, u2, u3);
  }
#pragma unroll
  for (int o = 1; o < 4; o <<= 1) {
    s0 += __shfl_xor_sync(~0u, s0, o); q0 += __shfl_xor_sync(~0u, q0, o);
    s1 += __shfl_xor_sync(~0u, s1, o); q1 += __shfl_xor_sync(~0u, q1, o);
  }
  if ((lane & 3) == 0) {
    stat_out[0] = make_float2(s0, q0);
    stat_out[8 * 8] = make_float2(s1, q1);
  }
}

constexpr int OPJ_CH = 8192 + 16384;
constexpr int OPJ_SMEM = 8 * OPJ_CH + 16384 + 1024 + 256;
__global__ void __launch_bounds__(256, 1) oproj_kernel(const uint8_t* __restrict__ resT, int early, int KID) {
  extern __shared__ uint8_t smraw[];
  const uint32_t sb = (smem_u32(smraw) + 1023) & ~1023u;
  const uint32_t res = sb + 8 * OPJ_CH, bars = res + 16384;
  const int tid = threadIdx.x, lane = tid & 31, warp = tid >> 5;
  const int tb = blockIdx.x >> 2, ct = blockIdx.x & 3;
  if (tid == 0) TS(KID, 0);
  pdl_trigger();
  if (tid == 0) {
    for (int i = 0; i < 9; i++) mbar_init(bars + i * 8, 1);
    mbar_fence_init();
  }
  __syncthreads();
  if (lane == 0) {
    const uint32_t fb = bars + warp * 8, st = sb + warp * OPJ_CH;
    mbar_expect(fb, OPJ_CH);
    const bool pre = early || pack_ready();
    if (pre) bulk_g2s(st + 8192, g_Wop + (ct * 8 + warp) * 16384, 16384, fb);
    if (tid == 0) TS(KID, 6);
    pdl_wait();
    if (tid == 0) TS(KID, 5);
    bulk_g2s(st, g_OT + (tb * 8 + warp) * 8192, 8192, fb);
    if (!pre) bulk_g2s(st + 8192, g_Wop + (ct * 8 + warp) * 16384, 16384, fb);
    if (warp == 7) {
      mbar_expect(bars + 64, 16384);
      bulk_g2s(res, resT + (tb * 8 + ct * 2) * 8192, 16384, bars + 64);
    }
  }
  if (warp >= 4) return;
  float acc[64];
#pragma unroll
  for (int i = 0; i < 64; i++) acc[i] = 0.f;
  fence_regs<64>(acc);
#pragma unroll 1
  for (int kc = 0; kc < 8; kc++) {
    const uint32_t st = sb + kc * OPJ_CH;
    mbar_wait(bars + kc * 8, 0);
    if (tid == 0 && kc == 0) TS(KID, 1);
    wg_fence();
#pragma unroll
    for (int ks = 0; ks < 4; ks++)
      wgmma_ss_tb_n128(acc, mkdesc(st + ks * 32, 16, 1024, 1), mkdesc(st + 8192 + ks * 4096, 2048, 128, 0), 1);
    wg_commit();
  }
  wg_wait<0>();
  fence_regs<64>(acc);
  if (tid == 0) TS(KID, 2);
  pdl_wait();
  mbar_wait(bars + 64, 0);
  const int r0 = tb * 64 + warp * 16 + (lane >> 2);
  residual_block(acc, res, warp, lane, g_statB + r0 * 8 + ct * 2);
  residual_block(acc + 32, res + 8192, warp, lane, g_statB + r0 * 8 + ct * 2 + 1);
  fence_async_smem();
  bar_sync(1, 128);
  if (tid == 0) {
    bulk_s2g(g_x1T + (tb * 8 + ct * 2) * 8192, res, 16384);
    TS(KID, 4);
    bulk_commit_wait_all();
    TS(KID, 3);
  }
}

constexpr int F1_STAGES = 5, F1_A = 16384, F1_B = 28672, F1_STAGE = F1_A + F1_B;
constexpr int F1_AUX = F1_STAGES * F1_STAGE;
constexpr int F1_SMEM = F1_AUX + 128 + 480 * 4 + 1024;
__global__ void __launch_bounds__(320, 1) ffn1_kernel(int early, int KID) {
  extern __shared__ uint8_t smraw[];
  const uint32_t sb = (smem_u32(smraw) + 1023) & ~1023u;
  const uint32_t bars = sb + F1_AUX;
  float* s_mean = reinterpret_cast<float*>(smraw + (sb - smem_u32(smraw)) + F1_AUX + 128);
  float* s_rstd = s_mean + 128;
  float* s_cs = s_rstd + 128;
  const int tid = threadIdx.x, lane = tid & 31, warp = tid >> 5;
  const int mb = blockIdx.x >> 3, fs = blockIdx.x & 7;
  if (tid == 0) TS(KID, 0);
  pdl_trigger();
  if (tid == 0) {
    for (int i = 0; i < F1_STAGES; i++) { mbar_init(bars + i * 8, 1); mbar_init(bars + (F1_STAGES + i) * 8, 8); }
    mbar_fence_init();
  }
  __syncthreads();
  const uint8_t* gA = g_x1T + (size_t)mb * 2 * 65536;
  const uint8_t* gB = g_W1p + (size_t)fs * 8 * F1_B;
  if (warp < F1_STAGES && lane == 0) {
    const uint32_t fb = bars + warp * 8, st = sb + warp * F1_STAGE;
    mbar_expect(fb, F1_STAGE);
    const bool pre = early || pack_ready();
    if (pre) bulk_g2s(st + F1_A, gB + warp * F1_B, F1_B, fb);
    if (tid == 0) TS(KID, 6);
    pdl_wait();
    if (tid == 0) TS(KID, 5);
    bulk_g2s(st, gA + warp * 8192, 8192, fb);
    bulk_g2s(st + 8192, gA + 65536 + warp * 8192, 8192, fb);
    if (!pre) bulk_g2s(st + F1_A, gB + warp * F1_B, F1_B, fb);
  }
  __syncwarp();
  if (warp == 8) {
    if (lane == 0) {
      pdl_wait();
#pragma unroll 1
      for (int kc = F1_STAGES; kc < 8; kc++) {
        const int s = kc - F1_STAGES;
        const uint32_t fb = bars + s * 8, st = sb + s * F1_STAGE;
        mbar_wait(bars + (F1_STAGES + s) * 8, 0);
        mbar_expect(fb, F1_STAGE);
        bulk_g2s(st + F1_A, gB + kc * F1_B, F1_B, fb);
        bulk_g2s(st, gA + kc * 8192, 8192, fb);
        bulk_g2s(st + 8192, gA + 65536 + kc * 8192, 8192, fb);
      }
    }
    return;
  }
  if (warp == 9) {
    pdl_wait();
#pragma unroll
    for (int i = 0; i < 4; i++) {
      float mean, rstd;
      row_stats(g_statB, mb * 128 + i * 32 + lane, mean, rstd);
      s_mean[i * 32 + lane] = mean; s_rstd[i * 32 + lane] = rstd;
    }
#pragma unroll
    for (int i = 0; i < 7; i++) s_cs[i * 32 + lane] = __ldcg(g_cs1 + fs * 224 + i * 32 + lane);
    asm volatile("bar.arrive 1, 288;" ::: "memory");
    return;
  }
  const int wg = warp >> 2, w4 = warp & 3;
  float acc[112];
#pragma unroll
  for (int i = 0; i < 112; i++) acc[i] = 0.f;
  fence_regs<112>(acc);
#pragma unroll 1
  for (int kc = 0; kc < 8; kc++) {
    const int s = kc % F1_STAGES;
    const uint32_t st = sb + s * F1_STAGE;
    mbar_wait(bars + s * 8, kc / F1_STAGES);
    if (tid == 0 && kc == 0) TS(KID, 1);
    wg_fence();
#pragma unroll
    for (int ks = 0; ks < 4; ks++)
      wgmma_ss_tb_n224(acc, mkdesc(st + wg * 8192 + ks * 32, 16, 1024, 1), mkdesc(st + F1_A + ks * 7168, 3584, 128, 0), 1);
    wg_commit();
    if (kc >= 1 && kc - 1 < 8 - F1_STAGES) {
      wg_wait<1>();
      if (lane == 0) mbar_arrive(bars + (F1_STAGES + kc - 1) * 8);
    }
  }
  wg_wait<0>();
  fence_regs<112>(acc);
  if (tid == 0) TS(KID, 2);
  pdl_wait();
  bar_sync(1, 288);
  const int g = lane >> 2, t = lane & 3;
  const int rl0 = wg * 64 + w4 * 16 + g;
  const float mean0 = s_mean[rl0], rstd0 = s_rstd[rl0], mean1 = s_mean[rl0 + 8], rstd1 = s_rstd[rl0 + 8];
  const uint32_t stg = sb + wg * 28672;
  const int rl = w4 * 16 + ((lane >> 3) & 1) * 8 + (lane & 7);
  constexpr float NL2E = -1.4426950408889634f;
#pragma unroll
  for (int j = 0; j < 28; j += 2) {
    const float2 ca = *reinterpret_cast<const float2*>(s_cs + 8 * j + 2 * t);
    const float2 cb = *reinterpret_cast<const float2*>(s_cs + 8 * j + 8 + 2 * t);
    const float* a = acc + 4 * j;
    float z[8];
    z[0] = (a[0] - mean0 * ca.x) * rstd0; z[1] = (a[1] - mean0 * ca.y) * rstd0;
    z[2] = (a[2] - mean1 * ca.x) * rstd1; z[3] = (a[3] - mean1 * ca.y) * rstd1;
    z[4] = (a[4] - mean0 * cb.x) * rstd0; z[5] = (a[5] - mean0 * cb.y) * rstd0;
    z[6] = (a[6] - mean1 * cb.x) * rstd1; z[7] = (a[7] - mean1 * cb.y) * rstd1;
#pragma unroll
    for (int i = 0; i < 8; i++) z[i] = __fdividef(z[i], 1.f + ex2f(z[i] * NL2E));
    const int blk = j >> 2, ch = (j & 3) + (lane >> 4);
    stsm4(stg + blk * 4096 + rl * 64 + ((ch ^ ((rl >> 1) & 3)) << 4), pack_bf16(z[0], z[1]), pack_bf16(z[2], z[3]), pack_bf16(z[4], z[5]),
          pack_bf16(z[6], z[7]));
  }
  fence_async_smem();
  bar_sync(2 + wg, 128);
  if ((tid & 127) == 0) {
    bulk_s2g(g_hT + ((size_t)(mb * 2 + wg) * 56 + fs * 7) * 4096, stg, 28672);
    if (tid == 0) TS(KID, 4);
    bulk_commit_wait_all();
    if (tid == 0) TS(KID, 3);
  }
}

constexpr int F2_STAGES = 5, F2_STAGE = 32768;
constexpr int F2_SMEM = F2_STAGES * F2_STAGE + 16384 + 32768 + 1024 + 256;
template <bool LAST>
__global__ void __cluster_dims__(2, 1, 1) __launch_bounds__(288, 1)
ffn2_kernel(const __grid_constant__ CUtensorMap mOut, int early, int KID) {
  extern __shared__ uint8_t smraw[];
  const uint32_t sb = (smem_u32(smraw) + 1023) & ~1023u;
  const uint32_t res = sb + F2_STAGES * F2_STAGE, recv = res + 16384, bars = recv + 32768;
  const int tid = threadIdx.x, lane = tid & 31, warp = tid >> 5;
  const int mb = blockIdx.x >> 3, nt = (blockIdx.x & 7) >> 1, kh = blockIdx.x & 1;
  if (tid == 0) TS(KID, 0);
  pdl_trigger();
  if (tid == 0) {
    for (int i = 0; i < F2_STAGES; i++) { mbar_init(bars + i * 8, 1); mbar_init(bars + (F2_STAGES + i) * 8, 8); }
    mbar_init(bars + 2 * F2_STAGES * 8, 1);
    mbar_fence_init();
  }
  __syncthreads();
  const uint8_t* gA = g_hT + ((size_t)mb * 2 * 56 + kh * 28) * 4096;
  const uint8_t* gB = g_W2p + ((size_t)nt * 28 + kh * 14) * 16384;
  if (warp < F2_STAGES && lane == 0) {
    const uint32_t fb = bars + warp * 8, st = sb + warp * F2_STAGE;
    mbar_expect(fb, F2_STAGE);
    const bool pre = early || pack_ready();
    if (pre) bulk_g2s(st + 16384, gB + warp * 16384, 16384, fb);
    if (tid == 0) TS(KID, 6);
    pdl_wait();
    bulk_g2s(st, gA + warp * 8192, 8192, fb);
    bulk_g2s(st + 8192, gA + 56 * 4096 + warp * 8192, 8192, fb);
    if (!pre) bulk_g2s(st + 16384, gB + warp * 16384, 16384, fb);
  }
  __syncwarp();
  if (warp == 8) {
    if (lane == 0) {
      pdl_wait();
      const uint32_t rb = bars + 2 * F2_STAGES * 8;
      mbar_expect(rb, 16384);
      bulk_g2s(res, g_x1T + ((mb * 2) * 8 + nt * 2 + kh) * 8192, 8192, rb);
      bulk_g2s(res + 8192, g_x1T + ((mb * 2 + 1) * 8 + nt * 2 + kh) * 8192, 8192, rb);
      if (LAST && blockIdx.x == 0) g_pack_done = 0;
      int s = 0, ph = 0;
#pragma unroll 1
      for (int kc = F2_STAGES; kc < 14; kc++) {
        const uint32_t fb = bars + s * 8, st = sb + s * F2_STAGE;
        mbar_wait(bars + (F2_STAGES + s) * 8, ph);
        mbar_expect(fb, F2_STAGE);
        bulk_g2s(st + 16384, gB + kc * 16384, 16384, fb);
        bulk_g2s(st, gA + kc * 8192, 8192, fb);
        bulk_g2s(st + 8192, gA + 56 * 4096 + kc * 8192, 8192, fb);
        if (++s == F2_STAGES) { s = 0; ph ^= 1; }
      }
    }
    return;
  }
  const int wg = warp >> 2, w4 = warp & 3;
  float acc[64];
#pragma unroll
  for (int i = 0; i < 64; i++) acc[i] = 0.f;
  fence_regs<64>(acc);
  {
    int s = 0, ph = 0, ps = 0;
#pragma unroll 1
    for (int kc = 0; kc < 14; kc++) {
      const uint32_t st = sb + s * F2_STAGE;
      mbar_wait(bars + s * 8, ph);
      if (tid == 0 && kc == 0) TS(KID, 1);
      wg_fence();
#pragma unroll
      for (int ks = 0; ks < 4; ks++)
        wgmma_ss_tb_n128(acc, mkdesc(st + wg * 8192 + (ks >> 1) * 4096 + (ks & 1) * 32, 16, 512, 2), mkdesc(st + 16384 + ks * 4096, 2048, 128, 0), 1);
      wg_commit();
      if (kc >= 1) {
        wg_wait<1>();
        if (lane == 0) mbar_arrive(bars + (F2_STAGES + ps) * 8);
      }
      ps = s;
      if (++s == F2_STAGES) { s = 0; ph ^= 1; }
    }
  }
  wg_wait<0>();
  fence_regs<64>(acc);
  if (tid == 0) TS(KID, 2);
  {
    uint32_t dst;
    asm volatile("mapa.shared::cluster.u32 %0, %1, %2;" : "=r"(dst) : "r"(recv + wg * 16384 + (tid & 127) * 16), "r"(kh ^ 1));
#pragma unroll
    for (int i = 0; i < 8; i++) {
      const float x0 = kh ? acc[4 * i] : acc[32 + 4 * i], x1 = kh ? acc[4 * i + 1] : acc[33 + 4 * i];
      const float x2 = kh ? acc[4 * i + 2] : acc[34 + 4 * i], x3 = kh ? acc[4 * i + 3] : acc[35 + 4 * i];
      asm volatile("st.shared::cluster.v4.f32 [%0], {%1,%2,%3,%4};" ::"r"(dst + i * 2048), "f"(x0), "f"(x1), "f"(x2), "f"(x3) : "memory");
    }
  }
  asm volatile("barrier.cluster.arrive.release.aligned;" ::: "memory");
  asm volatile("barrier.cluster.wait.acquire.aligned;" ::: "memory");
  if (tid == 0) TS(KID, 5);
  float fin[32];
#pragma unroll
  for (int i = 0; i < 8; i++) {
    float4 v;
    asm volatile("ld.shared.v4.f32 {%0,%1,%2,%3}, [%4];" : "=f"(v.x), "=f"(v.y), "=f"(v.z), "=f"(v.w) : "r"(recv + wg * 16384 + (tid & 127) * 16 + i * 2048));
    fin[4 * i] = v.x + (kh ? acc[32 + 4 * i] : acc[4 * i]);
    fin[4 * i + 1] = v.y + (kh ? acc[33 + 4 * i] : acc[4 * i + 1]);
    fin[4 * i + 2] = v.z + (kh ? acc[34 + 4 * i] : acc[4 * i + 2]);
    fin[4 * i + 3] = v.w + (kh ? acc[35 + 4 * i] : acc[4 * i + 3]);
  }
  pdl_wait();
  mbar_wait(bars + 2 * F2_STAGES * 8, 0);
  const int r0 = mb * 128 + wg * 64 + w4 * 16 + (lane >> 2);
  residual_block(fin, res + wg * 8192, w4, lane, g_statA + r0 * 8 + nt * 2 + kh);
  fence_async_smem();
  bar_sync(2 + wg, 128);
  if ((tid & 127) == 0) {
    if (LAST) tma2d_store(&mOut, nt * 128 + kh * 64, mb * 128 + wg * 64, res + wg * 8192);
    else bulk_s2g(g_x2T + ((mb * 2 + wg) * 8 + nt * 2 + kh) * 8192, res + wg * 8192, 8192);
    if (tid == 0) TS(KID, 4);
    bulk_commit_wait_all();
    if (tid == 0) TS(KID, 3);
    if (LAST && tid == 0 && blockIdx.x == 0) GT(1);
  }
}

typedef CUresult (*EncodeFn)(CUtensorMap*, CUtensorMapDataType, cuuint32_t, void*, const cuuint64_t*, const cuuint64_t*, const cuuint32_t*,
                             const cuuint32_t*, CUtensorMapInterleave, CUtensorMapSwizzle, CUtensorMapL2promotion, CUtensorMapFloatOOBfill);

CUtensorMap make_map(EncodeFn fn, const void* base, int rank, const cuuint64_t* dims, const cuuint64_t* strides, const cuuint32_t* box,
                     CUtensorMapSwizzle swz) {
  CUtensorMap m;
  cuuint32_t es[3] = {1, 1, 1};
  fn(&m, CU_TENSOR_MAP_DATA_TYPE_BFLOAT16, rank, const_cast<void*>(base), dims, strides, box, es, CU_TENSOR_MAP_INTERLEAVE_NONE, swz,
     CU_TENSOR_MAP_L2_PROMOTION_L2_256B, CU_TENSOR_MAP_FLOAT_OOB_FILL_NONE);
  return m;
}
CUtensorMap map2d(EncodeFn fn, const void* base, int rows, int cols, int box_rows) {
  cuuint64_t dims[2] = {(cuuint64_t)cols, (cuuint64_t)rows}, strides[1] = {(cuuint64_t)cols * 2};
  cuuint32_t box[2] = {64, (cuuint32_t)box_rows};
  return make_map(fn, base, 2, dims, strides, box, CU_TENSOR_MAP_SWIZZLE_128B);
}
template <typename... KArgs, typename... Args>
void launch(void (*kern)(KArgs...), int grid, int block, int smem, bool pdl, Args... args) {
  cudaLaunchConfig_t cfg = {};
  cfg.gridDim = dim3(grid);
  cfg.blockDim = dim3(block);
  cfg.dynamicSmemBytes = smem;
  cfg.stream = cudaStreamPerThread;
  cudaLaunchAttribute at[1];
  at[0].id = cudaLaunchAttributeProgrammaticStreamSerialization;
  at[0].val.programmaticStreamSerializationAllowed = 1;
  cfg.attrs = at;
  cfg.numAttrs = pdl ? 1 : 0;
  cudaLaunchKernelEx(&cfg, kern, args...);
}

}

extern "C" void kernel_launch(void* const* d_in, const int* in_sizes, int n_in, void* d_out, int out_size) {
  const bf16* x = (const bf16*)d_in[0];
  const bf16* wq = (const bf16*)d_in[1];
  const bf16* wk = (const bf16*)d_in[2];
  const bf16* wv = (const bf16*)d_in[3];
  const bf16* wo = (const bf16*)d_in[4];
  const bf16* w1 = (const bf16*)d_in[6];
  const bf16* w2 = (const bf16*)d_in[7];

  void* fp = nullptr;
  cudaDriverEntryPointQueryResult qr;
  cudaGetDriverEntryPoint("cuTensorMapEncodeTiled", &fp, cudaEnableDefault, &qr);
  EncodeFn fn = (EncodeFn)fp;
  const CUtensorMap mOut = map2d(fn, d_out, S_, D_, 64);

  cudaFuncSetAttribute(qkv_kernel<true>, cudaFuncAttributeMaxDynamicSharedMemorySize, QKV_SMEM);
  cudaFuncSetAttribute(qkv_kernel<false>, cudaFuncAttributeMaxDynamicSharedMemorySize, QKV_SMEM);
  cudaFuncSetAttribute(attn_kernel, cudaFuncAttributeMaxDynamicSharedMemorySize, ATT_SMEM);
  cudaFuncSetAttribute(oproj_kernel, cudaFuncAttributeMaxDynamicSharedMemorySize, OPJ_SMEM);
  cudaFuncSetAttribute(ffn1_kernel, cudaFuncAttributeMaxDynamicSharedMemorySize, F1_SMEM);
  cudaFuncSetAttribute(ffn2_kernel<false>, cudaFuncAttributeMaxDynamicSharedMemorySize, F2_SMEM);
  cudaFuncSetAttribute(ffn2_kernel<true>, cudaFuncAttributeMaxDynamicSharedMemorySize, F2_SMEM);
  void *pX0T, *pX2T;
  cudaGetSymbolAddress(&pX0T, g_x0T);
  cudaGetSymbolAddress(&pX2T, g_x2T);

  for (int layer = 0; layer < 2; layer++) {
    if (layer == 0) launch(qkv_kernel<true>, 128, 256, QKV_SMEM, false, x, wq, wk, wv);
    else launch(qkv_kernel<false>, 128, 256, QKV_SMEM, true, x, wq, wk, wv);
    launch(attn_kernel, layer == 0 ? 128 + (int)NPACK : 128, 512, ATT_SMEM, true, wo, w1, w2, 2 + layer * 5);
    launch(oproj_kernel, 128, 256, OPJ_SMEM, true, (const uint8_t*)(layer == 0 ? pX0T : pX2T), layer, 3 + layer * 5);
    launch(ffn1_kernel, 128, 320, F1_SMEM, true, layer, 4 + layer * 5);
    if (layer == 0) launch(ffn2_kernel<false>, 128, 288, F2_SMEM, true, mOut, layer, 5 + layer * 5);
    else launch(ffn2_kernel<true>, 128, 288, F2_SMEM, true, mOut, layer, 5 + layer * 5);
  }
}
```

```cpp
#include <cuda_runtime.h>
#include <cuda_bf16.h>
#include <cuda.h>
#include <stdint.h>

namespace {

typedef __nv_bfloat16 bf16;
constexpr int S_ = 2048, D_ = 512, F_ = 1792;
constexpr float LN_EPS = 1e-5f;
constexpr float QSCALE = 0.25f * 1.4426950408889634f;

constexpr uint32_t LUT_MASK_EVEN = 0x55, LUT_MASK_ODD = 0x5D;
constexpr float SAFE_SCORE_BOUND = 80.0f;

__device__ __align__(1024) bf16 g_Q[S_ * D_];
__device__ __align__(1024) uint8_t g_KV[S_ * 64];
__device__ __align__(1024) float g_kmax[32 * 16];
__device__ __align__(1024) uint8_t g_x0T[S_ * D_ * 2];
__device__ __align__(1024) uint8_t g_OT[S_ * D_ * 2];
__device__ __align__(1024) uint8_t g_x1T[S_ * D_ * 2];
__device__ __align__(1024) uint8_t g_x2T[S_ * D_ * 2];
__device__ __align__(1024) uint8_t g_hT[S_ * F_ * 2];
__device__ __align__(1024) float2 g_statA[S_ * 8];
__device__ __align__(1024) float2 g_statB[S_ * 8];
__device__ __align__(1024) float g_csQKV[4 * 136];
__device__ __align__(1024) float g_cs1[F_];
__device__ __align__(1024) uint8_t g_W1p[8 * 8 * 28672];
__device__ unsigned g_pack_done;
constexpr unsigned NPACK = 4;

#define TS(kid, slot)
#define GT(i)
__device__ __forceinline__ uint32_t smem_u32(const void* p) { return (uint32_t)__cvta_generic_to_shared(p); }
__device__ __forceinline__ void mbar_init(uint32_t b, uint32_t c) { asm volatile("mbarrier.init.shared::cta.b64 [%0], %1;" ::"r"(b), "r"(c)); }
__device__ __forceinline__ void mbar_fence_init() { asm volatile("fence.mbarrier_init.release.cluster;" ::: "memory"); }
__device__ __forceinline__ void mbar_expect(uint32_t b, uint32_t bytes) {
  asm volatile("mbarrier.arrive.expect_tx.shared::cta.b64 _, [%0], %1;" ::"r"(b), "r"(bytes) : "memory");
}
__device__ __forceinline__ void mbar_arrive(uint32_t b) { asm volatile("mbarrier.arrive.shared::cta.b64 _, [%0];" ::"r"(b) : "memory"); }
__device__ __forceinline__ void mbar_wait(uint32_t b, uint32_t ph) {
  asm volatile(
      "{.reg .pred p;\n"
      "LAB_WAIT:\n"
      "mbarrier.try_wait.parity.shared::cta.b64 p, [%0], %1;\n"
      "@p bra LAB_DONE;\n"
      "bra LAB_WAIT;\n"
      "LAB_DONE:\n}" ::"r"(b), "r"(ph) : "memory");
}
__device__ __forceinline__ void bulk_g2s(uint32_t dst, const void* src, uint32_t bytes, uint32_t bar) {
  asm volatile("cp.async.bulk.shared::cluster.global.mbarrier::complete_tx::bytes [%0], [%1], %2, [%3];" ::"r"(dst), "l"(src), "r"(bytes), "r"(bar) : "memory");
}
__device__ __forceinline__ void bulk_s2g(void* dst, uint32_t src, uint32_t bytes) {
  asm volatile("cp.async.bulk.global.shared::cta.bulk_group [%0], [%1], %2;" ::"l"(dst), "r"(src), "r"(bytes) : "memory");
}
__device__ __forceinline__ bool pack_ready() {
  unsigned v;
  asm volatile("ld.acquire.gpu.global.u32 %0, [%1];" : "=r"(v) : "l"(&g_pack_done) : "memory");
  return v == NPACK;
}
__device__ __forceinline__ void tma2d(uint32_t dst, const CUtensorMap* m, int c0, int c1, uint32_t bar) {
  asm volatile("cp.async.bulk.tensor.2d.shared::cluster.global.mbarrier::complete_tx::bytes [%0], [%1, {%3, %4}], [%2];"
               ::"r"(dst), "l"(m), "r"(bar), "r"(c0), "r"(c1) : "memory");
}
__device__ __forceinline__ void tma3d(uint32_t dst, const CUtensorMap* m, int c0, int c1, int c2, uint32_t bar) {
  asm volatile("cp.async.bulk.tensor.3d.shared::cluster.global.mbarrier::complete_tx::bytes [%0], [%1, {%3, %4, %5}], [%2];"
               ::"r"(dst), "l"(m), "r"(bar), "r"(c0), "r"(c1), "r"(c2) : "memory");
}
__device__ __forceinline__ void tmap_prefetch(const CUtensorMap* m) { asm volatile("prefetch.tensormap [%0];" ::"l"(m) : "memory"); }
__device__ __forceinline__ void tma2d_store(const CUtensorMap* m, int c0, int c1, uint32_t src) {
  asm volatile("cp.async.bulk.tensor.2d.global.shared::cta.bulk_group [%0, {%2, %3}], [%1];" ::"l"(m), "r"(src), "r"(c0), "r"(c1) : "memory");
}
__device__ __forceinline__ void bulk_commit_wait_all() {
  asm volatile("cp.async.bulk.commit_group;" ::: "memory");
  asm volatile("cp.async.bulk.wait_group 0;" ::: "memory");
}
__device__ __forceinline__ void fence_async_smem() { asm volatile("fence.proxy.async.shared::cta;" ::: "memory"); }
__device__ __forceinline__ void pdl_trigger() { asm volatile("griddepcontrol.launch_dependents;" ::: "memory"); }
__device__ __forceinline__ void pdl_wait() { asm volatile("griddepcontrol.wait;" ::: "memory"); }
__device__ __forceinline__ void bar_sync(int id, int n) { asm volatile("bar.sync %0, %1;" ::"r"(id), "r"(n) : "memory"); }
__device__ __forceinline__ void wg_fence() { asm volatile("wgmma.fence.sync.aligned;" ::: "memory"); }
__device__ __forceinline__ void wg_commit() { asm volatile("wgmma.commit_group.sync.aligned;" ::: "memory"); }
template <int N> __device__ __forceinline__ void wg_wait() { asm volatile("wgmma.wait_group.sync.aligned %0;" ::"n"(N) : "memory"); }
__device__ __forceinline__ uint64_t mkdesc(uint32_t addr, uint32_t lbo, uint32_t sbo, uint32_t swz) {
  return (uint64_t)((addr & 0x3FFFF) >> 4) | ((uint64_t)(lbo >> 4) << 16) | ((uint64_t)(sbo >> 4) << 32) | ((uint64_t)swz << 62);
}
template <int N> __device__ __forceinline__ void fence_regs(float* d) {
#pragma unroll
  for (int i = 0; i < N; i++) asm volatile("" : "+f"(d[i])::"memory");
}
template <int N> __device__ __forceinline__ void fence_regs_u(uint32_t* d) {
#pragma unroll
  for (int i = 0; i < N; i++) asm volatile("" : "+r"(d[i])::"memory");
}
__device__ __forceinline__ uint32_t pack_bf16(float lo, float hi) {
  uint32_t r;
  asm("cvt.rn.bf16x2.f32 %0, %1, %2;" : "=r"(r) : "f"(hi), "f"(lo));
  return r;
}
__device__ __forceinline__ float bf_lo(uint32_t u) { return __uint_as_float(u << 16); }
__device__ __forceinline__ float bf_hi(uint32_t u) { return __uint_as_float(u & 0xFFFF0000u); }
__device__ __forceinline__ float ex2f(float x) {
  float y;
  asm("ex2.approx.ftz.f32 %0, %1;" : "=f"(y) : "f"(x));
  return y;
}
__device__ __forceinline__ void stsm4(uint32_t a, uint32_t r0, uint32_t r1, uint32_t r2, uint32_t r3) {
  asm volatile("stmatrix.sync.aligned.m8n8.x4.shared.b16 [%0], {%1,%2,%3,%4};" ::"r"(a), "r"(r0), "r"(r1), "r"(r2), "r"(r3) : "memory");
}
__device__ __forceinline__ void ldsm4(uint32_t* r, uint32_t a) {
  asm volatile("ldmatrix.sync.aligned.m8n8.x4.shared.b16 {%0,%1,%2,%3}, [%4];" : "=r"(r[0]), "=r"(r[1]), "=r"(r[2]), "=r"(r[3]) : "r"(a) : "memory");
}
__device__ __forceinline__ void ldsm4t(uint32_t* r, uint32_t a) {
  asm volatile("ldmatrix.sync.aligned.m8n8.x4.trans.shared.b16 {%0,%1,%2,%3}, [%4];" : "=r"(r[0]), "=r"(r[1]), "=r"(r[2]), "=r"(r[3]) : "r"(a) : "memory");
}
__device__ __forceinline__ void mma16816(float* d, const uint32_t* a, uint32_t b0, uint32_t b1) {
  asm volatile("mma.sync.aligned.m16n8k16.row.col.f32.bf16.bf16.f32 {%0,%1,%2,%3}, {%4,%5,%6,%7}, {%8,%9}, {%0,%1,%2,%3};"
               : "+f"(d[0]), "+f"(d[1]), "+f"(d[2]), "+f"(d[3]) : "r"(a[0]), "r"(a[1]), "r"(a[2]), "r"(a[3]), "r"(b0), "r"(b1));
}
__device__ __forceinline__ void row_stats(const float2* __restrict__ st, int row, float& mean, float& rstd) {
  const float4* p = reinterpret_cast<const float4*>(st + row * 8);
  float s = 0.f, q = 0.f;
#pragma unroll
  for (int i = 0; i < 4; i++) {
    float4 v = __ldcg(p + i);
    s += v.x + v.z;
    q += v.y + v.w;
  }
  mean = s * (1.f / D_);
  float var = fmaxf(q * (1.f / D_) - mean * mean, 0.f);
  rstd = rsqrtf(var + LN_EPS);
}

__device__ __forceinline__ void wgmma_rs_n64(float* d, uint32_t a0, uint32_t a1, uint32_t a2, uint32_t a3, uint64_t descB, int scaleD){
  asm volatile("{.reg .pred p; setp.ne.b32 p, %37, 0; wgmma.mma_async.sync.aligned.m64n64k16.f32.bf16.bf16 {%0,%1,%2,%3,%4,%5,%6,%7,%8,%9,%10,%11,%12,%13,%14,%15,%16,%17,%18,%19,%20,%21,%22,%23,%24,%25,%26,%27,%28,%29,%30,%31}, {%32,%33,%34,%35}, %36, p, 1, 1, 0;}"
   : "+f"(d[0]),"+f"(d[1]),"+f"(d[2]),"+f"(d[3]),"+f"(d[4]),"+f"(d[5]),"+f"(d[6]),"+f"(d[7]),"+f"(d[8]),"+f"(d[9]),"+f"(d[10]),"+f"(d[11]),"+f"(d[12]),"+f"(d[13]),"+f"(d[14]),"+f"(d[15]),"+f"(d[16]),"+f"(d[17]),"+f"(d[18]),"+f"(d[19]),"+f"(d[20]),"+f"(d[21]),"+f"(d[22]),"+f"(d[23]),"+f"(d[24]),"+f"(d[25]),"+f"(d[26]),"+f"(d[27]),"+f"(d[28]),"+f"(d[29]),"+f"(d[30]),"+f"(d[31])
   : "r"(a0),"r"(a1),"r"(a2),"r"(a3),"l"(descB),"r"(scaleD));
}

__device__ __forceinline__ void wgmma_rs_tb_n24(float* d, uint32_t a0, uint32_t a1, uint32_t a2, uint32_t a3, uint64_t descB, int scaleD){
  asm volatile("{.reg .pred p; setp.ne.b32 p, %17, 0; wgmma.mma_async.sync.aligned.m64n24k16.f32.bf16.bf16 {%0,%1,%2,%3,%4,%5,%6,%7,%8,%9,%10,%11}, {%12,%13,%14,%15}, %16, p, 1, 1, 1;}"
   : "+f"(d[0]),"+f"(d[1]),"+f"(d[2]),"+f"(d[3]),"+f"(d[4]),"+f"(d[5]),"+f"(d[6]),"+f"(d[7]),"+f"(d[8]),"+f"(d[9]),"+f"(d[10]),"+f"(d[11])
   : "r"(a0),"r"(a1),"r"(a2),"r"(a3),"l"(descB),"r"(scaleD));
}

__device__ __forceinline__ void wgmma_ss_tb_n128(float* d, uint64_t descA, uint64_t descB, int scaleD){
  asm volatile("{.reg .pred p; setp.ne.b32 p, %66, 0; wgmma.mma_async.sync.aligned.m64n128k16.f32.bf16.bf16 {%0,%1,%2,%3,%4,%5,%6,%7,%8,%9,%10,%11,%12,%13,%14,%15,%16,%17,%18,%19,%20,%21,%22,%23,%24,%25,%26,%27,%28,%29,%30,%31,%32,%33,%34,%35,%36,%37,%38,%39,%40,%41,%42,%43,%44,%45,%46,%47,%48,%49,%50,%51,%52,%53,%54,%55,%56,%57,%58,%59,%60,%61,%62,%63}, %64, %65, p, 1, 1, 0, 1;}"
   : "+f"(d[0]),"+f"(d[1]),"+f"(d[2]),"+f"(d[3]),"+f"(d[4]),"+f"(d[5]),"+f"(d[6]),"+f"(d[7]),"+f"(d[8]),"+f"(d[9]),"+f"(d[10]),"+f"(d[11]),"+f"(d[12]),"+f"(d[13]),"+f"(d[14]),"+f"(d[15]),"+f"(d[16]),"+f"(d[17]),"+f"(d[18]),"+f"(d[19]),"+f"(d[20]),"+f"(d[21]),"+f"(d[22]),"+f"(d[23]),"+f"(d[24]),"+f"(d[25]),"+f"(d[26]),"+f"(d[27]),"+f"(d[28]),"+f"(d[29]),"+f"(d[30]),"+f"(d[31]),"+f"(d[32]),"+f"(d[33]),"+f"(d[34]),"+f"(d[35]),"+f"(d[36]),"+f"(d[37]),"+f"(d[38]),"+f"(d[39]),"+f"(d[40]),"+f"(d[41]),"+f"(d[42]),"+f"(d[43]),"+f"(d[44]),"+f"(d[45]),"+f"(d[46]),"+f"(d[47]),"+f"(d[48]),"+f"(d[49]),"+f"(d[50]),"+f"(d[51]),"+f"(d[52]),"+f"(d[53]),"+f"(d[54]),"+f"(d[55]),"+f"(d[56]),"+f"(d[57]),"+f"(d[58]),"+f"(d[59]),"+f"(d[60]),"+f"(d[61]),"+f"(d[62]),"+f"(d[63])
   : "l"(descA),"l"(descB),"r"(scaleD));
}

__device__ __forceinline__ void wgmma_ss_tb_n136(float* d, uint64_t descA, uint64_t descB, int scaleD){
  asm volatile("{.reg .pred p; setp.ne.b32 p, %70, 0; wgmma.mma_async.sync.aligned.m64n136k16.f32.bf16.bf16 {%0,%1,%2,%3,%4,%5,%6,%7,%8,%9,%10,%11,%12,%13,%14,%15,%16,%17,%18,%19,%20,%21,%22,%23,%24,%25,%26,%27,%28,%29,%30,%31,%32,%33,%34,%35,%36,%37,%38,%39,%40,%41,%42,%43,%44,%45,%46,%47,%48,%49,%50,%51,%52,%53,%54,%55,%56,%57,%58,%59,%60,%61,%62,%63,%64,%65,%66,%67}, %68, %69, p, 1, 1, 0, 1;}"
   : "+f"(d[0]),"+f"(d[1]),"+f"(d[2]),"+f"(d[3]),"+f"(d[4]),"+f"(d[5]),"+f"(d[6]),"+f"(d[7]),"+f"(d[8]),"+f"(d[9]),"+f"(d[10]),"+f"(d[11]),"+f"(d[12]),"+f"(d[13]),"+f"(d[14]),"+f"(d[15]),"+f"(d[16]),"+f"(d[17]),"+f"(d[18]),"+f"(d[19]),"+f"(d[20]),"+f"(d[21]),"+f"(d[22]),"+f"(d[23]),"+f"(d[24]),"+f"(d[25]),"+f"(d[26]),"+f"(d[27]),"+f"(d[28]),"+f"(d[29]),"+f"(d[30]),"+f"(d[31]),"+f"(d[32]),"+f"(d[33]),"+f"(d[34]),"+f"(d[35]),"+f"(d[36]),"+f"(d[37]),"+f"(d[38]),"+f"(d[39]),"+f"(d[40]),"+f"(d[41]),"+f"(d[42]),"+f"(d[43]),"+f"(d[44]),"+f"(d[45]),"+f"(d[46]),"+f"(d[47]),"+f"(d[48]),"+f"(d[49]),"+f"(d[50]),"+f"(d[51]),"+f"(d[52]),"+f"(d[53]),"+f"(d[54]),"+f"(d[55]),"+f"(d[56]),"+f"(d[57]),"+f"(d[58]),"+f"(d[59]),"+f"(d[60]),"+f"(d[61]),"+f"(d[62]),"+f"(d[63]),"+f"(d[64]),"+f"(d[65]),"+f"(d[66]),"+f"(d[67])
   : "l"(descA),"l"(descB),"r"(scaleD));
}

__device__ __forceinline__ void wgmma_ss_tb_n224(float* d, uint64_t descA, uint64_t descB, int scaleD){
  asm volatile("{.reg .pred p; setp.ne.b32 p, %114, 0; wgmma.mma_async.sync.aligned.m64n224k16.f32.bf16.bf16 {%0,%1,%2,%3,%4,%5,%6,%7,%8,%9,%10,%11,%12,%13,%14,%15,%16,%17,%18,%19,%20,%21,%22,%23,%24,%25,%26,%27,%28,%29,%30,%31,%32,%33,%34,%35,%36,%37,%38,%39,%40,%41,%42,%43,%44,%45,%46,%47,%48,%49,%50,%51,%52,%53,%54,%55,%56,%57,%58,%59,%60,%61,%62,%63,%64,%65,%66,%67,%68,%69,%70,%71,%72,%73,%74,%75,%76,%77,%78,%79,%80,%81,%82,%83,%84,%85,%86,%87,%88,%89,%90,%91,%92,%93,%94,%95,%96,%97,%98,%99,%100,%101,%102,%103,%104,%105,%106,%107,%108,%109,%110,%111}, %112, %113, p, 1, 1, 0, 1;}"
   : "+f"(d[0]),"+f"(d[1]),"+f"(d[2]),"+f"(d[3]),"+f"(d[4]),"+f"(d[5]),"+f"(d[6]),"+f"(d[7]),"+f"(d[8]),"+f"(d[9]),"+f"(d[10]),"+f"(d[11]),"+f"(d[12]),"+f"(d[13]),"+f"(d[14]),"+f"(d[15]),"+f"(d[16]),"+f"(d[17]),"+f"(d[18]),"+f"(d[19]),"+f"(d[20]),"+f"(d[21]),"+f"(d[22]),"+f"(d[23]),"+f"(d[24]),"+f"(d[25]),"+f"(d[26]),"+f"(d[27]),"+f"(d[28]),"+f"(d[29]),"+f"(d[30]),"+f"(d[31]),"+f"(d[32]),"+f"(d[33]),"+f"(d[34]),"+f"(d[35]),"+f"(d[36]),"+f"(d[37]),"+f"(d[38]),"+f"(d[39]),"+f"(d[40]),"+f"(d[41]),"+f"(d[42]),"+f"(d[43]),"+f"(d[44]),"+f"(d[45]),"+f"(d[46]),"+f"(d[47]),"+f"(d[48]),"+f"(d[49]),"+f"(d[50]),"+f"(d[51]),"+f"(d[52]),"+f"(d[53]),"+f"(d[54]),"+f"(d[55]),"+f"(d[56]),"+f"(d[57]),"+f"(d[58]),"+f"(d[59]),"+f"(d[60]),"+f"(d[61]),"+f"(d[62]),"+f"(d[63]),"+f"(d[64]),"+f"(d[65]),"+f"(d[66]),"+f"(d[67]),"+f"(d[68]),"+f"(d[69]),"+f"(d[70]),"+f"(d[71]),"+f"(d[72]),"+f"(d[73]),"+f"(d[74]),"+f"(d[75]),"+f"(d[76]),"+f"(d[77]),"+f"(d[78]),"+f"(d[79]),"+f"(d[80]),"+f"(d[81]),"+f"(d[82]),"+f"(d[83]),"+f"(d[84]),"+f"(d[85]),"+f"(d[86]),"+f"(d[87]),"+f"(d[88]),"+f"(d[89]),"+f"(d[90]),"+f"(d[91]),"+f"(d[92]),"+f"(d[93]),"+f"(d[94]),"+f"(d[95]),"+f"(d[96]),"+f"(d[97]),"+f"(d[98]),"+f"(d[99]),"+f"(d[100]),"+f"(d[101]),"+f"(d[102]),"+f"(d[103]),"+f"(d[104]),"+f"(d[105]),"+f"(d[106]),"+f"(d[107]),"+f"(d[108]),"+f"(d[109]),"+f"(d[110]),"+f"(d[111])
   : "l"(descA),"l"(descB),"r"(scaleD));
}

constexpr int QKV_CH = 8192 + 16384;
constexpr int QKV_KV = 8 * QKV_CH;
constexpr int QKV_AUX = QKV_KV + 8192;
constexpr int QKV_SMEM = QKV_AUX + 2048 + 1024;

template <bool FIRST>
__global__ void __launch_bounds__(256, 1) qkv_kernel(const __grid_constant__ CUtensorMap mX, const __grid_constant__ CUtensorMap mWq,
                                                      const bf16* __restrict__ wk, const bf16* __restrict__ wv) {
  extern __shared__ uint8_t smraw[];
  const uint32_t sb = (smem_u32(smraw) + 1023) & ~1023u;
  uint8_t* sp = smraw + (sb - smem_u32(smraw));
  float* s_mean = reinterpret_cast<float*>(sp + QKV_AUX);
  float* s_rstd = s_mean + 64;
  float* s_cs = s_rstd + 64;
  float* s_km = s_cs + 128;
  const uint32_t bars = sb + QKV_AUX + 1536;
  const int tid = threadIdx.x, lane = tid & 31, warp = tid >> 5;
  const int tb = blockIdx.x >> 2, hg = blockIdx.x & 3;
  const int KID = FIRST ? 1 : 6;
  if (tid == 0) TS(KID, 0);
  if (FIRST && tid == 0 && blockIdx.x == 0) GT(0);
  pdl_trigger();
  if (tid == 0) {
    tmap_prefetch(&mWq);
    if (FIRST) tmap_prefetch(&mX);
    for (int i = 0; i < 8; i++) mbar_init(bars + i * 8, 1);
    mbar_fence_init();
  }
  __syncthreads();
  if (tid == 128) {
#pragma unroll 1
    for (int kc = 0; kc < 8; kc++) {
      mbar_expect(bars + kc * 8, QKV_CH);
      tma3d(sb + kc * QKV_CH + 8192, &mWq, 0, kc * 64, hg * 2, bars + kc * 8);
    }
  } else if (tid == 160) {
    if (!FIRST) { TS(KID, 6); pdl_wait(); TS(KID, 5); }
#pragma unroll 1
    for (int kc = 0; kc < 8; kc++) {
      if (FIRST) tma2d(sb + kc * QKV_CH, &mX, kc * 64, tb * 64, bars + kc * 8);
      else bulk_g2s(sb + kc * QKV_CH, g_x2T + (tb * 8 + kc) * 8192, 8192, bars + kc * 8);
    }
  }
  __syncwarp();
  const int g = lane >> 2, t = lane & 3;
  if (warp >= 4) {
    const int t1 = tid & 127, w4 = warp & 3;
    const bf16* wkv = (hg < 2 ? wk : wv) + (hg & 1) * 8;
    {
      uint4 v[4];
#pragma unroll
      for (int i = 0; i < 4; i++) v[i] = __ldg(reinterpret_cast<const uint4*>(wkv + (size_t)(i * 128 + t1) * 16));
#pragma unroll
      for (int i = 0; i < 4; i++) *reinterpret_cast<uint4*>(sp + QKV_KV + (i * 128 + t1) * 16) = v[i];
    }
    float mean0, rstd0, mean1, rstd1;
    const int rl0 = w4 * 16 + g, r0 = tb * 64 + rl0;
    if (!FIRST) {
      pdl_wait();
      row_stats(g_statA, r0, mean0, rstd0);
      row_stats(g_statA, r0 + 8, mean1, rstd1);
      s_cs[t1] = __ldcg(g_csQKV + hg * 136 + t1);
    }
    bar_sync(2, 128);
    float kv[4] = {0.f, 0.f, 0.f, 0.f}, ones[4] = {0.f, 0.f, 0.f, 0.f}, cs[8];
    float rs0 = 0.f, rq0 = 0.f, rs1 = 0.f, rq1 = 0.f;
#pragma unroll
    for (int i = 0; i < 8; i++) cs[i] = 0.f;
    const int arow = w4 * 16 + (lane & 15);
#pragma unroll 1
    for (int kc = 0; kc < 8; kc++) {
      mbar_wait(bars + kc * 8, 0);
      const uint32_t st = sb + kc * QKV_CH;
#pragma unroll
      for (int ks = 0; ks < 4; ks++) {
        uint32_t a[4], b[4];
        ldsm4(a, st + arow * 128 + (((ks * 2 + (lane >> 4)) ^ (arow & 7)) << 4));
        ldsm4t(b, sb + QKV_KV + (kc * 64 + ks * 16 + (lane & 15)) * 16);
        mma16816(kv, a, b[0], b[1]);
        if (FIRST) {
          const float f0 = bf_lo(a[0]), f1 = bf_hi(a[0]), f2 = bf_lo(a[2]), f3 = bf_hi(a[2]);
          const float h0 = bf_lo(a[1]), h1 = bf_hi(a[1]), h2 = bf_lo(a[3]), h3 = bf_hi(a[3]);
          rs0 += (f0 + f1) + (f2 + f3); rq0 += f0 * f0 + f1 * f1 + f2 * f2 + f3 * f3;
          rs1 += (h0 + h1) + (h2 + h3); rq1 += h0 * h0 + h1 * h1 + h2 * h2 + h3 * h3;
          const uint32_t one[4] = {0x3F803F80u, 0x3F803F80u, 0x3F803F80u, 0x3F803F80u};
          mma16816(ones, one, b[0], b[1]);
        }
      }
      if (FIRST) {
        const int cg = t1 >> 3, kr = t1 & 7;
        const uint8_t* bp = sp + kc * QKV_CH + 8192 + (cg >> 3) * 8192 + kr * 128 + (((cg & 7) ^ kr) << 4);
#pragma unroll
        for (int kg = 0; kg < 8; kg++) {
          const uint4 v = *reinterpret_cast<const uint4*>(bp + kg * 1024);
          cs[0] += bf_lo(v.x); cs[1] += bf_hi(v.x); cs[2] += bf_lo(v.y); cs[3] += bf_hi(v.y);
          cs[4] += bf_lo(v.z); cs[5] += bf_hi(v.z); cs[6] += bf_lo(v.w); cs[7] += bf_hi(v.w);
        }
      }
    }
    float ck0, ck1;
    if (FIRST) {
#pragma unroll
      for (int o = 1; o < 4; o <<= 1) {
        rs0 += __shfl_xor_sync(~0u, rs0, o); rq0 += __shfl_xor_sync(~0u, rq0, o);
        rs1 += __shfl_xor_sync(~0u, rs1, o); rq1 += __shfl_xor_sync(~0u, rq1, o);
      }
      mean0 = rs0 * (1.f / D_); mean1 = rs1 * (1.f / D_);
      rstd0 = rsqrtf(fmaxf(rq0 * (1.f / D_) - mean0 * mean0, 0.f) + LN_EPS);
      rstd1 = rsqrtf(fmaxf(rq1 * (1.f / D_) - mean1 * mean1, 0.f) + LN_EPS);
#pragma unroll
      for (int i = 0; i < 8; i++) {
#pragma unroll
        for (int o = 1; o < 8; o <<= 1) cs[i] += __shfl_xor_sync(~0u, cs[i], o);
      }
      if ((t1 & 7) == 0) {
#pragma unroll
        for (int i = 0; i < 8; i++) s_cs[(t1 >> 3) * 8 + i] = cs[i];
        if (tb == 0) {
#pragma unroll
          for (int i = 0; i < 8; i++) g_csQKV[hg * 136 + (t1 >> 3) * 8 + i] = cs[i];
        }
      }
      ck0 = ones[0]; ck1 = ones[1];
      if (tb == 0 && w4 == 0 && g == 0) { g_csQKV[hg * 136 + 128 + 2 * t] = ck0; g_csQKV[hg * 136 + 128 + 2 * t + 1] = ck1; }
      if (hg == 0 && t1 == 0) {
#pragma unroll 1
        for (int kc = 0; kc < 8; kc++) bulk_s2g(g_x0T + (tb * 8 + kc) * 8192, sb + kc * QKV_CH, 8192);
        asm volatile("cp.async.bulk.commit_group;" ::: "memory");
      }
    } else {
      ck0 = __ldcg(g_csQKV + hg * 136 + 128 + 2 * t);
      ck1 = __ldcg(g_csQKV + hg * 136 + 128 + 2 * t + 1);
    }
    if (t == 0) { s_mean[rl0] = mean0; s_rstd[rl0] = rstd0; s_mean[rl0 + 8] = mean1; s_rstd[rl0 + 8] = rstd1; }
    asm volatile("bar.arrive 1, 256;" ::: "memory");
    uint32_t u0 = pack_bf16((kv[0] - mean0 * ck0) * rstd0, (kv[1] - mean0 * ck1) * rstd0);
    uint32_t u1 = pack_bf16((kv[2] - mean1 * ck0) * rstd1, (kv[3] - mean1 * ck1) * rstd1);
    uint8_t* kvp = g_KV + (r0 >> 8) * 16384;
    const int kk = r0 & 255;
    if (hg < 2) {
      *reinterpret_cast<uint32_t*>(kvp + (kk >> 3) * 256 + hg * 128 + (kk & 7) * 16 + t * 4) = u0;
      *reinterpret_cast<uint32_t*>(kvp + ((kk + 8) >> 3) * 256 + hg * 128 + (kk & 7) * 16 + t * 4) = u1;
      float m0 = fmaxf(fabsf(bf_lo(u0)), fabsf(bf_lo(u1))), m1 = fmaxf(fabsf(bf_hi(u0)), fabsf(bf_hi(u1)));
      if (!(bf_lo(u0) == bf_lo(u0)) || !(bf_lo(u1) == bf_lo(u1))) m0 = __int_as_float(0x7f800000);
      if (!(bf_hi(u0) == bf_hi(u0)) || !(bf_hi(u1) == bf_hi(u1))) m1 = __int_as_float(0x7f800000);
#pragma unroll
      for (int o = 4; o < 32; o <<= 1) { m0 = fmaxf(m0, __shfl_xor_sync(~0u, m0, o)); m1 = fmaxf(m1, __shfl_xor_sync(~0u, m1, o)); }
      if (g == 0) { s_km[w4 * 8 + 2 * t] = m0; s_km[w4 * 8 + 2 * t + 1] = m1; }
      bar_sync(2, 128);
      if (t1 < 8) g_kmax[tb * 16 + hg * 8 + t1] = fmaxf(fmaxf(s_km[t1], s_km[8 + t1]), fmaxf(s_km[16 + t1], s_km[24 + t1]));
    } else {
      const uint32_t mask = ((r0 >> 6) & 1) ? LUT_MASK_ODD : LUT_MASK_EVEN;
      if ((mask >> ((r0 >> 3) & 7)) & 1) u0 ^= 0x80008000u;
      if ((mask >> (((r0 + 8) >> 3) & 7)) & 1) u1 ^= 0x80008000u;
      *reinterpret_cast<uint32_t*>(kvp + 8192 + (hg - 2) * 4096 + kk * 16 + t * 4) = u0;
      *reinterpret_cast<uint32_t*>(kvp + 8192 + (hg - 2) * 4096 + (kk + 8) * 16 + t * 4) = u1;
    }
    if (FIRST && hg == 0 && t1 == 0) asm volatile("cp.async.bulk.wait_group 0;" ::: "memory");
    return;
  }
  float acc[64];
#pragma unroll
  for (int i = 0; i < 64; i++) acc[i] = 0.f;
  fence_regs<64>(acc);
#pragma unroll 1
  for (int kc = 0; kc < 8; kc++) {
    const uint32_t st = sb + kc * QKV_CH;
    mbar_wait(bars + kc * 8, 0);
    if (tid == 0 && kc == 0) TS(KID, 1);
    wg_fence();
#pragma unroll
    for (int ks = 0; ks < 4; ks++)
      wgmma_ss_tb_n128(acc, mkdesc(st + ks * 32, 16, 1024, 1), mkdesc(st + 8192 + ks * 2048, 8192, 1024, 1), 1);
    wg_commit();
  }
  wg_wait<0>();
  fence_regs<64>(acc);
  if (tid == 0) TS(KID, 2);
  bar_sync(1, 256);
  if (!FIRST) pdl_wait();
  if (tid == 0) TS(KID, 4);
  const int rl0 = warp * 16 + g, r0 = tb * 64 + rl0;
  const float mean0 = s_mean[rl0], mean1 = s_mean[rl0 + 8];
  const float q0 = s_rstd[rl0] * QSCALE, q1 = s_rstd[rl0 + 8] * QSCALE;
  uint32_t* qp0 = reinterpret_cast<uint32_t*>(g_Q + (size_t)r0 * D_ + hg * 128) + t;
  uint32_t* qp1 = qp0 + 8 * (D_ / 2);
#pragma unroll
  for (int j = 0; j < 16; j++) {
    const float2 c = *reinterpret_cast<const float2*>(s_cs + 8 * j + 2 * t);
    const float* a = acc + 4 * j;
    qp0[4 * j] = pack_bf16((a[0] - mean0 * c.x) * q0, (a[1] - mean0 * c.y) * q0);
    qp1[4 * j] = pack_bf16((a[2] - mean1 * c.x) * q1, (a[3] - mean1 * c.y) * q1);
  }
  if (tid == 0) TS(KID, 3);
}

constexpr int ATT_SMEM = 31 * 1024 + 192 * 1024 + 2048 + 1024;
constexpr int KVCH = 20480;
constexpr float LUT_MAGIC = 382.875f;

template <uint32_t MASK>
__device__ __forceinline__ void exp_pack(const float* s, uint32_t* p, uint32_t lutlane) {
#pragma unroll
  for (int i = 0; i < 16; i++) {
    if ((MASK >> (i / 2)) & 1) {
      const uint32_t b0 = __float_as_uint(s[2 * i] + LUT_MAGIC), b1 = __float_as_uint(s[2 * i + 1] + LUT_MAGIC);
      uint32_t c0, c1, w;
      asm volatile("ld.shared.u16 %0, [%1+2];" : "=r"(c0) : "r"((b0 & 0x7F80u) | lutlane));
      asm volatile("ld.shared.u32 %0, [%1];" : "=r"(c1) : "r"((b1 & 0x7F80u) | lutlane));
      asm("prmt.b32 %0, %1, %2, 0x6521;" : "=r"(w) : "r"(b0), "r"(b1));
      p[i] = w + c0 + c1;
    } else {
      p[i] = pack_bf16(ex2f(s[2 * i]), ex2f(s[2 * i + 1]));
    }
  }
}

__device__ __noinline__ void pack_weights(const CUtensorMap* mW1, const bf16* __restrict__ wo, const bf16* __restrict__ w2, int cta, uint8_t* smraw) {
  const int tid = threadIdx.x;
  const uint32_t sb = (smem_u32(smraw) + 1023) & ~1023u;
  uint8_t* sp = smraw + (sb - smem_u32(smraw));
  constexpr int IMG = 28672, NBUF = 7;
  const uint32_t bars = sb + NBUF * IMG;
  float* part = reinterpret_cast<float*>(sp + NBUF * IMG + 64);
  if (tid == 0) {
    for (int i = 0; i < NBUF; i++) mbar_init(bars + i * 8, 1);
    mbar_fence_init();
    for (int i = 0; i < NBUF; i++) { mbar_expect(bars + i * 8, IMG); tma3d(sb + i * IMG, mW1, 0, (i & 7) * 64, (cta * 2 + (i >> 3)) * 7, bars + i * 8); }
  }
  if (tid == 32) {
    constexpr uint32_t WO_B = D_ * D_ * 2 / NPACK, W2_B = F_ * D_ * 2 / NPACK;
    for (uint32_t o = 0; o < WO_B; o += 16384) asm volatile("cp.async.bulk.prefetch.L2.global [%0], %1;" ::"l"((const char*)wo + cta * WO_B + o), "r"(16384));
    for (uint32_t o = 0; o < W2_B; o += 16384) asm volatile("cp.async.bulk.prefetch.L2.global [%0], %1;" ::"l"((const char*)w2 + cta * W2_B + o), "r"(16384));
  }
  __syncthreads();
  const int cg = tid % 28, rg = tid / 28;
  float cs[8];
#pragma unroll
  for (int i = 0; i < 8; i++) cs[i] = 0.f;
#pragma unroll 1
  for (int it = 0; it < 16; it++) {
    const int buf = it % NBUF;
    mbar_wait(bars + buf * 8, (it / NBUF) & 1);
    if (tid == 0) { bulk_s2g(g_W1p + (size_t)(cta * 16 + it) * IMG, sb + buf * IMG, IMG); asm volatile("cp.async.bulk.commit_group;" ::: "memory"); }
    if (tid < 448) {
#pragma unroll
      for (int r = 0; r < 4; r++) {
        const int row = rg * 4 + r;
        const uint4 v = *reinterpret_cast<const uint4*>(sp + buf * IMG + (cg >> 2) * 4096 + row * 64 + (((cg & 3) ^ ((row >> 1) & 3)) << 4));
        cs[0] += bf_lo(v.x); cs[1] += bf_hi(v.x); cs[2] += bf_lo(v.y); cs[3] += bf_hi(v.y);
        cs[4] += bf_lo(v.z); cs[5] += bf_hi(v.z); cs[6] += bf_lo(v.w); cs[7] += bf_hi(v.w);
      }
    }
    if ((it & 7) == 7) {
      if (tid < 448) {
#pragma unroll
        for (int i = 0; i < 8; i++) { part[rg * 224 + cg * 8 + i] = cs[i]; cs[i] = 0.f; }
      }
      __syncthreads();
      if (tid < 224) {
        float s = 0.f;
#pragma unroll
        for (int q = 0; q < 16; q++) s += part[q * 224 + tid];
        g_cs1[(cta * 2 + (it >> 3)) * 224 + tid] = s;
      }
    }
    __syncthreads();
    if (tid == 0 && it + NBUF < 16) {
      asm volatile("cp.async.bulk.wait_group.read 0;" ::: "memory");
      const int nx = it + NBUF;
      mbar_expect(bars + buf * 8, IMG);
      tma3d(sb + buf * IMG, mW1, 0, (nx & 7) * 64, (cta * 2 + (nx >> 3)) * 7, bars + buf * 8);
    }
  }
  if (tid == 0) asm volatile("cp.async.bulk.wait_group 0;" ::: "memory");
  __threadfence();
  __syncthreads();
  if (tid == 0) asm volatile("red.release.gpu.global.add.u32 [%0], 1;" ::"l"(&g_pack_done) : "memory");
}

__global__ void __launch_bounds__(512, 1) attn_kernel(const __grid_constant__ CUtensorMap mW1, const bf16* __restrict__ wo, const bf16* __restrict__ w2, int KID) {
  extern __shared__ uint8_t smraw[];
  const uint32_t sbase = smem_u32(smraw);
  const uint32_t bars = sbase;
  const uint32_t kred = sbase + 128;
  const uint32_t qst = sbase + 4096;
  const uint32_t LUT = (sbase + 4096 + 16384 + 32767) & ~32767u;
  const uint32_t KS = LUT + 32768;
  if (blockIdx.x >= 128) { pdl_trigger(); pack_weights(&mW1, wo, w2, blockIdx.x - 128, smraw); return; }
  uint8_t* sm0 = smraw - sbase;
  const int tid = threadIdx.x, lane = tid & 31, wg = tid >> 7, warp = (tid >> 5) & 3;
  if (tid == 0) TS(KID, 0);
  pdl_trigger();
  if (tid == 0) {
    for (int i = 0; i < 8; i++) mbar_init(bars + i * 8, 1);
    mbar_fence_init();
  }
  for (int i = tid; i < 256 * 32; i += 512) {
    const int idx = i >> 5;
    const float v = exp2f((idx + 0.5f) * (1.f / 256.f) + 0.125f);
    const int target = (v < 2.f) ? (int)rintf(128.f * v) - 128 : (int)rintf(64.f * v);
    reinterpret_cast<uint32_t*>(sm0 + LUT)[i] = (uint32_t)(target - (idx >> 1)) << 16;
  }
  for (int i = tid; i < S_; i += 512) {
    const uint32_t mask = ((i >> 6) & 1) ? LUT_MASK_ODD : LUT_MASK_EVEN;
    const uint32_t o = ((mask >> ((i >> 3) & 7)) & 1) ? 0xBF80BF80u : 0x3F803F80u;
    *reinterpret_cast<uint4*>(sm0 + KS + (i >> 8) * KVCH + 16384 + (i & 255) * 16) = make_uint4(o, o, o, o);
  }
  fence_async_smem();
  __syncthreads();
  if (tid == 0) TS(KID, 5);
  pdl_wait();
  if (tid == 0) TS(KID, 4);
  if (tid == 0) {
    mbar_expect(bars, 16384 + 2048);
    bulk_g2s(KS, g_KV, 16384, bars);
    bulk_g2s(kred, g_kmax, 2048, bars);
  } else if (tid == 128) {
    mbar_expect(bars + 8, 16384);
    bulk_g2s(KS + KVCH, g_KV + 16384, 16384, bars + 8);
  }
  const int g = lane >> 2, t = lane & 3;
  uint32_t qq[2][4];
#pragma unroll
  for (int tile = 0; tile < 2; tile++) {
    const int row0 = (blockIdx.x * 8 + wg * 2 + tile) * 64 + warp * 16 + g;
    const uint32_t* qp = reinterpret_cast<const uint32_t*>(g_Q);
    qq[tile][0] = __ldcg(qp + (size_t)row0 * 8 + t);
    qq[tile][1] = __ldcg(qp + (size_t)(row0 + 8) * 8 + t);
    qq[tile][2] = __ldcg(qp + (size_t)row0 * 8 + 4 + t);
    qq[tile][3] = __ldcg(qp + (size_t)(row0 + 8) * 8 + 4 + t);
  }
  if (lane == 0 && tid >= 256 && tid < 448) {
    const int c = (tid >> 5) - 6;
    mbar_expect(bars + c * 8, 16384);
    bulk_g2s(KS + c * KVCH, g_KV + c * 16384, 16384, bars + c * 8);
  }
  __syncwarp();
  mbar_wait(bars, 0);
  if (tid == 0) TS(KID, 6);
  float km[4];
  {
    const float4* kr = reinterpret_cast<const float4*>(sm0 + kred);
    float4 m = kr[lane];
#pragma unroll
    for (int i = 1; i < 4; i++) {
      const float4 v = kr[lane + 32 * i];
      m.x = fmaxf(m.x, v.x); m.y = fmaxf(m.y, v.y); m.z = fmaxf(m.z, v.z); m.w = fmaxf(m.w, v.w);
    }
#pragma unroll
    for (int o = 4; o < 32; o <<= 1) {
      m.x = fmaxf(m.x, __shfl_xor_sync(~0u, m.x, o)); m.y = fmaxf(m.y, __shfl_xor_sync(~0u, m.y, o));
      m.z = fmaxf(m.z, __shfl_xor_sync(~0u, m.z, o)); m.w = fmaxf(m.w, __shfl_xor_sync(~0u, m.w, o));
    }
    const float ax = __shfl_sync(~0u, m.x, t >> 1), ay = __shfl_sync(~0u, m.y, t >> 1), az = __shfl_sync(~0u, m.z, t >> 1), aw = __shfl_sync(~0u, m.w, t >> 1);
    const float bx = __shfl_sync(~0u, m.x, 2 + (t >> 1)), by = __shfl_sync(~0u, m.y, 2 + (t >> 1)), bz = __shfl_sync(~0u, m.z, 2 + (t >> 1)),
                bw = __shfl_sync(~0u, m.w, 2 + (t >> 1));
    km[0] = (t & 1) ? az : ax; km[1] = (t & 1) ? aw : ay;
    km[2] = (t & 1) ? bz : bx; km[3] = (t & 1) ? bw : by;
  }
  uint32_t unsafe_bits = 0;
#pragma unroll
  for (int tile = 0; tile < 2; tile++) {
    const uint32_t* q = qq[tile];
    float b0 = fabsf(bf_lo(q[0])) * km[0] + fabsf(bf_hi(q[0])) * km[1] + fabsf(bf_lo(q[2])) * km[2] + fabsf(bf_hi(q[2])) * km[3];
    float b1 = fabsf(bf_lo(q[1])) * km[0] + fabsf(bf_hi(q[1])) * km[1] + fabsf(bf_lo(q[3])) * km[2] + fabsf(bf_hi(q[3])) * km[3];
    b0 += __shfl_xor_sync(~0u, b0, 1); b0 += __shfl_xor_sync(~0u, b0, 2);
    b1 += __shfl_xor_sync(~0u, b1, 1); b1 += __shfl_xor_sync(~0u, b1, 2);
    const uint32_t bad = !(b0 <= SAFE_SCORE_BOUND && b1 <= SAFE_SCORE_BOUND);
    uint32_t u;
    asm volatile("{.reg .pred p, r; setp.ne.u32 p, %1, 0; bar.red.or.pred r, %2, 128, p; selp.u32 %0, 1, 0, r;}"
                 : "=r"(u) : "r"(bad), "r"(1 + wg) : "memory");
    unsafe_bits |= (__any_sync(~0u, u) ? 1u : 0u) << tile;
    asm volatile("st.shared.v4.u32 [%0], {%1,%2,%3,%4};" ::"r"(qst + tile * 8192 + tid * 16), "r"(q[0]), "r"(q[1]), "r"(q[2]), "r"(q[3]) : "memory");
  }
  const uint32_t lutlane = LUT | (lane * 4);
  constexpr uint64_t KSTEP = (64 * 32) >> 4, VSTEP = (16 * 16) >> 4;
  constexpr uint64_t KJUMP = (KVCH - 3 * 2048) >> 4, VJUMP = (KVCH - 4096) >> 4;
#pragma unroll 1
  for (int tile = 0; tile < 2; tile++) {
    uint32_t q[4];
    asm volatile("ld.shared.v4.u32 {%0,%1,%2,%3}, [%4];" : "=r"(q[0]), "=r"(q[1]), "=r"(q[2]), "=r"(q[3]) : "r"(qst + tile * 8192 + tid * 16) : "memory");
    const uint32_t unsafe = (unsafe_bits >> tile) & 1;
    float o[12];
#pragma unroll
    for (int i = 0; i < 12; i++) o[i] = 0.f;
    uint64_t kd = mkdesc(KS, 128, 256, 0);
    uint64_t vd = mkdesc(KS + 8192, 128, 4096, 0);
    if (!unsafe) {
      float s[32];
      uint32_t p[16];
      if (tid == 0 && tile == 0) TS(KID, 1);
      fence_regs<12>(o);
      wg_fence();
      wgmma_rs_n64(s, q[0], q[1], q[2], q[3], kd, 0); kd += KSTEP;
      wg_commit();
#pragma unroll 1
      for (int c = 0; c < 8; c++) {
        if (c < 7) mbar_wait(bars + (c + 1) * 8, 0);
#pragma unroll 1
        for (int j = 0; j < 2; j++) {
          wg_wait<0>(); fence_regs<32>(s); fence_regs<12>(o); fence_regs_u<16>(p);
          exp_pack<LUT_MASK_EVEN>(s, p, lutlane);
          wg_fence();
#pragma unroll
          for (int k = 0; k < 4; k++) { wgmma_rs_tb_n24(o, p[4 * k], p[4 * k + 1], p[4 * k + 2], p[4 * k + 3], vd, 1); vd += VSTEP; }
          wgmma_rs_n64(s, q[0], q[1], q[2], q[3], kd, 0); kd += j ? KJUMP : KSTEP;
          wg_commit();
          wg_wait<0>(); fence_regs<32>(s); fence_regs<12>(o); fence_regs_u<16>(p);
          exp_pack<LUT_MASK_ODD>(s, p, lutlane);
          wg_fence();
#pragma unroll
          for (int k = 0; k < 4; k++) { wgmma_rs_tb_n24(o, p[4 * k], p[4 * k + 1], p[4 * k + 2], p[4 * k + 3], vd, 1); vd += VSTEP; }
          wgmma_rs_n64(s, q[0], q[1], q[2], q[3], kd, 0); kd += KSTEP;
          wg_commit();
        }
        vd += VJUMP;
      }
      wg_wait<0>(); fence_regs<12>(o); fence_regs<32>(s);
    } else {
      for (int c = 0; c < 8; c++) mbar_wait(bars + c * 8, 0);
      float m0 = -INFINITY, m1 = -INFINITY;
#pragma unroll 1
      for (int kb = 0; kb < S_ / 16; kb++) {
        uint32_t kf[4];
        float sa[4] = {0.f, 0.f, 0.f, 0.f}, sc[4] = {0.f, 0.f, 0.f, 0.f};
        ldsm4(kf, KS + (kb >> 4) * KVCH + (kb & 15) * 512 + lane * 16);
        mma16816(sa, q, kf[0], kf[1]);
        mma16816(sc, q, kf[2], kf[3]);
        m0 = fmaxf(fmaxf(m0, fmaxf(sa[0], sa[1])), fmaxf(sc[0], sc[1]));
        m1 = fmaxf(fmaxf(m1, fmaxf(sa[2], sa[3])), fmaxf(sc[2], sc[3]));
      }
      m0 = fmaxf(m0, __shfl_xor_sync(~0u, m0, 1)); m0 = fmaxf(m0, __shfl_xor_sync(~0u, m0, 2));
      m1 = fmaxf(m1, __shfl_xor_sync(~0u, m1, 1)); m1 = fmaxf(m1, __shfl_xor_sync(~0u, m1, 2));
#pragma unroll 1
      for (int kb = 0; kb < S_ / 16; kb++) {
        uint32_t kf[4], vf[4], ef[4], a[4];
        float sa[4] = {0.f, 0.f, 0.f, 0.f}, sc[4] = {0.f, 0.f, 0.f, 0.f};
        const uint32_t chb = KS + (kb >> 4) * KVCH;
        ldsm4(kf, chb + (kb & 15) * 512 + lane * 16);
        const uint32_t krow = chb + 8192 + ((kb & 15) * 16 + (lane & 15)) * 16;
        ldsm4t(vf, krow + (lane >> 4) * 4096);
        ldsm4t(ef, krow + 8192);
        mma16816(sa, q, kf[0], kf[1]);
        mma16816(sc, q, kf[2], kf[3]);
        const uint32_t mask = ((kb >> 2) & 1) ? LUT_MASK_ODD : LUT_MASK_EVEN;
        const uint32_t sg0 = ((mask >> ((2 * kb) & 7)) & 1) ? 0x80008000u : 0u, sg1 = ((mask >> ((2 * kb + 1) & 7)) & 1) ? 0x80008000u : 0u;
        a[0] = pack_bf16(ex2f(sa[0] - m0), ex2f(sa[1] - m0)) ^ sg0;
        a[1] = pack_bf16(ex2f(sa[2] - m1), ex2f(sa[3] - m1)) ^ sg0;
        a[2] = pack_bf16(ex2f(sc[0] - m0), ex2f(sc[1] - m0)) ^ sg1;
        a[3] = pack_bf16(ex2f(sc[2] - m1), ex2f(sc[3] - m1)) ^ sg1;
        mma16816(o, a, vf[0], vf[1]);
        mma16816(o + 4, a, vf[2], vf[3]);
        mma16816(o + 8, a, ef[0], ef[1]);
      }
    }
    const float r0 = 1.f / o[8], r1 = 1.f / o[10];
    const int row0 = (blockIdx.x * 8 + wg * 2 + tile) * 64 + warp * 16 + g;
    const int tok = row0 >> 5, h0 = row0 & 31, h1 = h0 + 8, tr = tok & 63;
    uint8_t* ob = g_OT + (tok >> 6) * 65536 + tr * 128 + t * 4;
    uint8_t* o0 = ob + (h0 >> 2) * 8192;
    uint8_t* o1 = ob + (h1 >> 2) * 8192;
    const int c0 = (h0 & 3) * 2, sw = tr & 7;
    *reinterpret_cast<uint32_t*>(o0 + ((c0 ^ sw) << 4)) = pack_bf16(o[0] * r0, o[1] * r0);
    *reinterpret_cast<uint32_t*>(o1 + ((c0 ^ sw) << 4)) = pack_bf16(o[2] * r1, o[3] * r1);
    *reinterpret_cast<uint32_t*>(o0 + (((c0 + 1) ^ sw) << 4)) = pack_bf16(o[4] * r0, o[5] * r0);
    *reinterpret_cast<uint32_t*>(o1 + (((c0 + 1) ^ sw) << 4)) = pack_bf16(o[6] * r1, o[7] * r1);
    if (tid == 0 && tile == 0) TS(KID, 2);
  }
  if (tid == 0) TS(KID, 3);
}

__device__ __forceinline__ void residual_block(const float* a, uint32_t tile, int warp, int lane, float2* stat_out  ) {
  const int rl = warp * 16 + ((lane >> 3) & 1) * 8 + (lane & 7);
  const uint32_t rowa = tile + rl * 128;
  float s0 = 0.f, q0 = 0.f, s1 = 0.f, q1 = 0.f;
#pragma unroll
  for (int j = 0; j < 8; j += 2) {
    const uint32_t ad = rowa + (((j + (lane >> 4)) ^ (rl & 7)) << 4);
    uint32_t r[4];
    ldsm4(r, ad);
    const float* c = a + 4 * j;
    const uint32_t u0 = pack_bf16(bf_lo(r[0]) + c[0], bf_hi(r[0]) + c[1]);
    const uint32_t u1 = pack_bf16(bf_lo(r[1]) + c[2], bf_hi(r[1]) + c[3]);
    const uint32_t u2 = pack_bf16(bf_lo(r[2]) + c[4], bf_hi(r[2]) + c[5]);
    const uint32_t u3 = pack_bf16(bf_lo(r[3]) + c[6], bf_hi(r[3]) + c[7]);
    s0 += (bf_lo(u0) + bf_hi(u0)) + (bf_lo(u2) + bf_hi(u2));
    q0 += bf_lo(u0) * bf_lo(u0) + bf_hi(u0) * bf_hi(u0) + bf_lo(u2) * bf_lo(u2) + bf_hi(u2) * bf_hi(u2);
    s1 += (bf_lo(u1) + bf_hi(u1)) + (bf_lo(u3) + bf_hi(u3));
    q1 += bf_lo(u1) * bf_lo(u1) + bf_hi(u1) * bf_hi(u1) + bf_lo(u3) * bf_lo(u3) + bf_hi(u3) * bf_hi(u3);
    stsm4(ad, u0, u1, u2, u3);
  }
#pragma unroll
  for (int o = 1; o < 4; o <<= 1) {
    s0 += __shfl_xor_sync(~0u, s0, o); q0 += __shfl_xor_sync(~0u, q0, o);
    s1 += __shfl_xor_sync(~0u, s1, o); q1 += __shfl_xor_sync(~0u, q1, o);
  }
  if ((lane & 3) == 0) {
    stat_out[0] = make_float2(s0, q0);
    stat_out[8 * 8] = make_float2(s1, q1);
  }
}

constexpr int OPJ_CH = 8192 + 16384;
constexpr int OPJ_SMEM = 8 * OPJ_CH + 16384 + 1024 + 256;
__global__ void __launch_bounds__(192, 1) oproj_kernel(const __grid_constant__ CUtensorMap mW, const uint8_t* __restrict__ resT, int KID) {
  extern __shared__ uint8_t smraw[];
  const uint32_t sb = (smem_u32(smraw) + 1023) & ~1023u;
  const uint32_t res = sb + 8 * OPJ_CH, bars = res + 16384;
  const int tid = threadIdx.x, lane = tid & 31, warp = tid >> 5;
  const int tb = blockIdx.x >> 2, ct = blockIdx.x & 3;
  if (tid == 0) TS(KID, 0);
  pdl_trigger();
  if (tid == 0) {
    tmap_prefetch(&mW);
    for (int i = 0; i < 9; i++) mbar_init(bars + i * 8, 1);
    mbar_fence_init();
  }
  __syncthreads();
  if (tid == 128) {
#pragma unroll 1
    for (int kc = 0; kc < 8; kc++) {
      mbar_expect(bars + kc * 8, OPJ_CH);
      tma3d(sb + kc * OPJ_CH + 8192, &mW, 0, kc * 64, ct * 2, bars + kc * 8);
    }
  } else if (tid == 160) {
    TS(KID, 6);
    pdl_wait();
    TS(KID, 5);
#pragma unroll 1
    for (int kc = 0; kc < 8; kc++) bulk_g2s(sb + kc * OPJ_CH, g_OT + (tb * 8 + kc) * 8192, 8192, bars + kc * 8);
    mbar_expect(bars + 64, 16384);
    bulk_g2s(res, resT + (tb * 8 + ct * 2) * 8192, 16384, bars + 64);
  }
  if (warp >= 4) return;
  float acc[64];
#pragma unroll
  for (int i = 0; i < 64; i++) acc[i] = 0.f;
  fence_regs<64>(acc);
#pragma unroll 1
  for (int kc = 0; kc < 8; kc++) {
    const uint32_t st = sb + kc * OPJ_CH;
    mbar_wait(bars + kc * 8, 0);
    if (tid == 0 && kc == 0) TS(KID, 1);
    wg_fence();
#pragma unroll
    for (int ks = 0; ks < 4; ks++)
      wgmma_ss_tb_n128(acc, mkdesc(st + ks * 32, 16, 1024, 1), mkdesc(st + 8192 + ks * 2048, 8192, 1024, 1), 1);
    wg_commit();
  }
  wg_wait<0>();
  fence_regs<64>(acc);
  if (tid == 0) TS(KID, 2);
  pdl_wait();
  mbar_wait(bars + 64, 0);
  const int r0 = tb * 64 + warp * 16 + (lane >> 2);
  residual_block(acc, res, warp, lane, g_statB + r0 * 8 + ct * 2);
  residual_block(acc + 32, res + 8192, warp, lane, g_statB + r0 * 8 + ct * 2 + 1);
  fence_async_smem();
  bar_sync(1, 128);
  if (tid == 0) {
    bulk_s2g(g_x1T + (tb * 8 + ct * 2) * 8192, res, 16384);
    TS(KID, 4);
    bulk_commit_wait_all();
    TS(KID, 3);
  }
}

constexpr int F1_STAGES = 5, F1_A = 16384, F1_B = 28672, F1_STAGE = F1_A + F1_B;
constexpr int F1_AUX = F1_STAGES * F1_STAGE;
constexpr int F1_SMEM = F1_AUX + 128 + 480 * 4 + 1024;
__global__ void __launch_bounds__(352, 1) ffn1_kernel(int early, int KID) {
  extern __shared__ uint8_t smraw[];
  const uint32_t sb = (smem_u32(smraw) + 1023) & ~1023u;
  const uint32_t bars = sb + F1_AUX;
  float* s_mean = reinterpret_cast<float*>(smraw + (sb - smem_u32(smraw)) + F1_AUX + 128);
  float* s_rstd = s_mean + 128;
  float* s_cs = s_rstd + 128;
  const int tid = threadIdx.x, lane = tid & 31, warp = tid >> 5;
  const int mb = blockIdx.x >> 3, fs = blockIdx.x & 7;
  if (tid == 0) TS(KID, 0);
  pdl_trigger();
  if (tid == 0) {
    for (int i = 0; i < F1_STAGES; i++) { mbar_init(bars + i * 8, 1); mbar_init(bars + (F1_STAGES + i) * 8, 8); }
    mbar_fence_init();
  }
  __syncthreads();
  const uint8_t* gA = g_x1T + (size_t)mb * 2 * 65536;
  const uint8_t* gB = g_W1p + (size_t)fs * 8 * F1_B;
  if (warp == 8) {
    if (lane == 0) {
      const bool pre = early || pack_ready();
      if (!pre) pdl_wait();
#pragma unroll 1
      for (int kc = 0; kc < F1_STAGES; kc++) {
        mbar_expect(bars + kc * 8, F1_STAGE);
        bulk_g2s(sb + kc * F1_STAGE + F1_A, gB + kc * F1_B, F1_B, bars + kc * 8);
      }
      pdl_wait();
#pragma unroll 1
      for (int kc = F1_STAGES; kc < 8; kc++) {
        const int s = kc - F1_STAGES;
        const uint32_t fb = bars + s * 8, st = sb + s * F1_STAGE;
        mbar_wait(bars + (F1_STAGES + s) * 8, 0);
        mbar_expect(fb, F1_STAGE);
        bulk_g2s(st, gA + kc * 8192, 8192, fb);
        bulk_g2s(st + 8192, gA + 65536 + kc * 8192, 8192, fb);
        bulk_g2s(st + F1_A, gB + kc * F1_B, F1_B, fb);
      }
    }
    return;
  }
  if (warp == 10) {
    if (lane == 0) {
      TS(KID, 6);
      pdl_wait();
      TS(KID, 5);
#pragma unroll 1
      for (int kc = 0; kc < F1_STAGES; kc++) {
        bulk_g2s(sb + kc * F1_STAGE, gA + kc * 8192, 8192, bars + kc * 8);
        bulk_g2s(sb + kc * F1_STAGE + 8192, gA + 65536 + kc * 8192, 8192, bars + kc * 8);
      }
    }
    return;
  }
  if (warp == 9) {
    pdl_wait();
#pragma unroll
    for (int i = 0; i < 4; i++) {
      float mean, rstd;
      row_stats(g_statB, mb * 128 + i * 32 + lane, mean, rstd);
      s_mean[i * 32 + lane] = mean; s_rstd[i * 32 + lane] = rstd;
    }
#pragma unroll
    for (int i = 0; i < 7; i++) s_cs[i * 32 + lane] = __ldcg(g_cs1 + fs * 224 + i * 32 + lane);
    asm volatile("bar.arrive 1, 288;" ::: "memory");
    return;
  }
  const int wg = warp >> 2, w4 = warp & 3;
  float acc[112];
#pragma unroll
  for (int i = 0; i < 112; i++) acc[i] = 0.f;
  fence_regs<112>(acc);
#pragma unroll 1
  for (int kc = 0; kc < 8; kc++) {
    const int s = kc % F1_STAGES;
    const uint32_t st = sb + s * F1_STAGE;
    mbar_wait(bars + s * 8, kc / F1_STAGES);
    if (tid == 0 && kc == 0) TS(KID, 1);
    wg_fence();
#pragma unroll
    for (int ks = 0; ks < 4; ks++)
      wgmma_ss_tb_n224(acc, mkdesc(st + wg * 8192 + ks * 32, 16, 1024, 1), mkdesc(st + F1_A + ks * 1024, 4096, 512, 2), 1);
    wg_commit();
    if (kc >= 1 && kc - 1 < 8 - F1_STAGES) {
      wg_wait<1>();
      if (lane == 0) mbar_arrive(bars + (F1_STAGES + kc - 1) * 8);
    }
  }
  wg_wait<0>();
  fence_regs<112>(acc);
  if (tid == 0) TS(KID, 2);
  pdl_wait();
  bar_sync(1, 288);
  const int g = lane >> 2, t = lane & 3;
  const int rl0 = wg * 64 + w4 * 16 + g;
  const float mean0 = s_mean[rl0], rstd0 = s_rstd[rl0], mean1 = s_mean[rl0 + 8], rstd1 = s_rstd[rl0 + 8];
  const uint32_t stg = sb + wg * 28672;
  const int rl = w4 * 16 + ((lane >> 3) & 1) * 8 + (lane & 7);
  constexpr float NL2E = -1.4426950408889634f;
#pragma unroll
  for (int j = 0; j < 28; j += 2) {
    const float2 ca = *reinterpret_cast<const float2*>(s_cs + 8 * j + 2 * t);
    const float2 cb = *reinterpret_cast<const float2*>(s_cs + 8 * j + 8 + 2 * t);
    const float* a = acc + 4 * j;
    float z[8];
    z[0] = (a[0] - mean0 * ca.x) * rstd0; z[1] = (a[1] - mean0 * ca.y) * rstd0;
    z[2] = (a[2] - mean1 * ca.x) * rstd1; z[3] = (a[3] - mean1 * ca.y) * rstd1;
    z[4] = (a[4] - mean0 * cb.x) * rstd0; z[5] = (a[5] - mean0 * cb.y) * rstd0;
    z[6] = (a[6] - mean1 * cb.x) * rstd1; z[7] = (a[7] - mean1 * cb.y) * rstd1;
#pragma unroll
    for (int i = 0; i < 8; i++) z[i] = __fdividef(z[i], 1.f + ex2f(z[i] * NL2E));
    const int blk = j >> 2, ch = (j & 3) + (lane >> 4);
    stsm4(stg + blk * 4096 + rl * 64 + ((ch ^ ((rl >> 1) & 3)) << 4), pack_bf16(z[0], z[1]), pack_bf16(z[2], z[3]), pack_bf16(z[4], z[5]),
          pack_bf16(z[6], z[7]));
  }
  fence_async_smem();
  bar_sync(2 + wg, 128);
  if ((tid & 127) == 0) {
    bulk_s2g(g_hT + ((size_t)(mb * 2 + wg) * 56 + fs * 7) * 4096, stg, 28672);
    if (tid == 0) TS(KID, 4);
    bulk_commit_wait_all();
    if (tid == 0) TS(KID, 3);
  }
}

constexpr int F2_STAGES = 5, F2_STAGE = 32768;
constexpr int F2_SMEM = F2_STAGES * F2_STAGE + 16384 + 32768 + 1024 + 256;
template <bool LAST>
__global__ void __cluster_dims__(2, 1, 1) __launch_bounds__(320, 1)
ffn2_kernel(const __grid_constant__ CUtensorMap mW, const __grid_constant__ CUtensorMap mOut, int KID) {
  extern __shared__ uint8_t smraw[];
  const uint32_t sb = (smem_u32(smraw) + 1023) & ~1023u;
  const uint32_t res = sb + F2_STAGES * F2_STAGE, recv = res + 16384, bars = recv + 32768;
  const int tid = threadIdx.x, lane = tid & 31, warp = tid >> 5;
  const int mb = blockIdx.x >> 3, nt = (blockIdx.x & 7) >> 1, kh = blockIdx.x & 1;
  if (tid == 0) TS(KID, 0);
  pdl_trigger();
  if (tid == 0) {
    tmap_prefetch(&mW);
    if (LAST) tmap_prefetch(&mOut);
    for (int i = 0; i < F2_STAGES; i++) { mbar_init(bars + i * 8, 1); mbar_init(bars + (F2_STAGES + i) * 8, 8); }
    mbar_init(bars + 2 * F2_STAGES * 8, 1);
    mbar_fence_init();
  }
  __syncthreads();
  const uint8_t* gA = g_hT + ((size_t)mb * 2 * 56 + kh * 28) * 4096;
  if (warp == 8) {
    if (lane == 0) {
#pragma unroll 1
      for (int kc = 0; kc < F2_STAGES; kc++) {
        mbar_expect(bars + kc * 8, F2_STAGE);
        tma3d(sb + kc * F2_STAGE + 16384, &mW, 0, kh * 896 + kc * 64, nt * 2, bars + kc * 8);
      }
      pdl_wait();
      if (LAST && blockIdx.x == 0) g_pack_done = 0;
      int s = 0, ph = 0;
#pragma unroll 1
      for (int kc = F2_STAGES; kc < 14; kc++) {
        const uint32_t fb = bars + s * 8, st = sb + s * F2_STAGE;
        mbar_wait(bars + (F2_STAGES + s) * 8, ph);
        mbar_expect(fb, F2_STAGE);
        bulk_g2s(st, gA + kc * 8192, 8192, fb);
        bulk_g2s(st + 8192, gA + 56 * 4096 + kc * 8192, 8192, fb);
        tma3d(st + 16384, &mW, 0, kh * 896 + kc * 64, nt * 2, fb);
        if (++s == F2_STAGES) { s = 0; ph ^= 1; }
      }
    }
    return;
  }
  if (warp == 9) {
    if (lane == 0) {
      TS(KID, 6);
      pdl_wait();
#pragma unroll 1
      for (int kc = 0; kc < F2_STAGES; kc++) {
        bulk_g2s(sb + kc * F2_STAGE, gA + kc * 8192, 8192, bars + kc * 8);
        bulk_g2s(sb + kc * F2_STAGE + 8192, gA + 56 * 4096 + kc * 8192, 8192, bars + kc * 8);
      }
      const uint32_t rb = bars + 2 * F2_STAGES * 8;
      mbar_expect(rb, 16384);
      bulk_g2s(res, g_x1T + ((mb * 2) * 8 + nt * 2 + kh) * 8192, 8192, rb);
      bulk_g2s(res + 8192, g_x1T + ((mb * 2 + 1) * 8 + nt * 2 + kh) * 8192, 8192, rb);
    }
    return;
  }
  const int wg = warp >> 2, w4 = warp & 3;
  float acc[64];
#pragma unroll
  for (int i = 0; i < 64; i++) acc[i] = 0.f;
  fence_regs<64>(acc);
  {
    int s = 0, ph = 0, ps = 0;
#pragma unroll 1
    for (int kc = 0; kc < 14; kc++) {
      const uint32_t st = sb + s * F2_STAGE;
      mbar_wait(bars + s * 8, ph);
      if (tid == 0 && kc == 0) TS(KID, 1);
      wg_fence();
#pragma unroll
      for (int ks = 0; ks < 4; ks++)
        wgmma_ss_tb_n128(acc, mkdesc(st + wg * 8192 + (ks >> 1) * 4096 + (ks & 1) * 32, 16, 512, 2), mkdesc(st + 16384 + ks * 2048, 8192, 1024, 1), 1);
      wg_commit();
      if (kc >= 1) {
        wg_wait<1>();
        if (lane == 0) mbar_arrive(bars + (F2_STAGES + ps) * 8);
      }
      ps = s;
      if (++s == F2_STAGES) { s = 0; ph ^= 1; }
    }
  }
  wg_wait<0>();
  fence_regs<64>(acc);
  if (tid == 0) TS(KID, 2);
  {
    uint32_t dst;
    asm volatile("mapa.shared::cluster.u32 %0, %1, %2;" : "=r"(dst) : "r"(recv + wg * 16384 + (tid & 127) * 16), "r"(kh ^ 1));
#pragma unroll
    for (int i = 0; i < 8; i++) {
      const float x0 = kh ? acc[4 * i] : acc[32 + 4 * i], x1 = kh ? acc[4 * i + 1] : acc[33 + 4 * i];
      const float x2 = kh ? acc[4 * i + 2] : acc[34 + 4 * i], x3 = kh ? acc[4 * i + 3] : acc[35 + 4 * i];
      asm volatile("st.shared::cluster.v4.f32 [%0], {%1,%2,%3,%4};" ::"r"(dst + i * 2048), "f"(x0), "f"(x1), "f"(x2), "f"(x3) : "memory");
    }
  }
  asm volatile("barrier.cluster.arrive.release.aligned;" ::: "memory");
  asm volatile("barrier.cluster.wait.acquire.aligned;" ::: "memory");
  if (tid == 0) TS(KID, 5);
  float fin[32];
#pragma unroll
  for (int i = 0; i < 8; i++) {
    float4 v;
    asm volatile("ld.shared.v4.f32 {%0,%1,%2,%3}, [%4];" : "=f"(v.x), "=f"(v.y), "=f"(v.z), "=f"(v.w) : "r"(recv + wg * 16384 + (tid & 127) * 16 + i * 2048));
    fin[4 * i] = v.x + (kh ? acc[32 + 4 * i] : acc[4 * i]);
    fin[4 * i + 1] = v.y + (kh ? acc[33 + 4 * i] : acc[4 * i + 1]);
    fin[4 * i + 2] = v.z + (kh ? acc[34 + 4 * i] : acc[4 * i + 2]);
    fin[4 * i + 3] = v.w + (kh ? acc[35 + 4 * i] : acc[4 * i + 3]);
  }
  pdl_wait();
  mbar_wait(bars + 2 * F2_STAGES * 8, 0);
  const int r0 = mb * 128 + wg * 64 + w4 * 16 + (lane >> 2);
  residual_block(fin, res + wg * 8192, w4, lane, g_statA + r0 * 8 + nt * 2 + kh);
  fence_async_smem();
  bar_sync(2 + wg, 128);
  if ((tid & 127) == 0) {
    if (LAST) tma2d_store(&mOut, nt * 128 + kh * 64, mb * 128 + wg * 64, res + wg * 8192);
    else bulk_s2g(g_x2T + ((mb * 2 + wg) * 8 + nt * 2 + kh) * 8192, res + wg * 8192, 8192);
    if (tid == 0) TS(KID, 4);
    bulk_commit_wait_all();
    if (tid == 0) TS(KID, 3);
    if (LAST && tid == 0 && blockIdx.x == 0) GT(1);
  }
}

typedef CUresult (*EncodeFn)(CUtensorMap*, CUtensorMapDataType, cuuint32_t, void*, const cuuint64_t*, const cuuint64_t*, const cuuint32_t*,
                             const cuuint32_t*, CUtensorMapInterleave, CUtensorMapSwizzle, CUtensorMapL2promotion, CUtensorMapFloatOOBfill);

CUtensorMap make_map(EncodeFn fn, const void* base, int rank, const cuuint64_t* dims, const cuuint64_t* strides, const cuuint32_t* box,
                     CUtensorMapSwizzle swz) {
  CUtensorMap m;
  cuuint32_t es[3] = {1, 1, 1};
  fn(&m, CU_TENSOR_MAP_DATA_TYPE_BFLOAT16, rank, const_cast<void*>(base), dims, strides, box, es, CU_TENSOR_MAP_INTERLEAVE_NONE, swz,
     CU_TENSOR_MAP_L2_PROMOTION_NONE, CU_TENSOR_MAP_FLOAT_OOB_FILL_NONE);
  return m;
}
CUtensorMap map2d(EncodeFn fn, const void* base, int rows, int cols, int box_rows) {
  cuuint64_t dims[2] = {(cuuint64_t)cols, (cuuint64_t)rows}, strides[1] = {(cuuint64_t)cols * 2};
  cuuint32_t box[2] = {64, (cuuint32_t)box_rows};
  return make_map(fn, base, 2, dims, strides, box, CU_TENSOR_MAP_SWIZZLE_128B);
}
CUtensorMap map3d(EncodeFn fn, const void* base, int rows, int cols, int inner, int box_rows, int box_blocks) {
  cuuint64_t dims[3] = {(cuuint64_t)inner, (cuuint64_t)rows, (cuuint64_t)(cols / inner)};
  cuuint64_t strides[2] = {(cuuint64_t)cols * 2, (cuuint64_t)inner * 2};
  cuuint32_t box[3] = {(cuuint32_t)inner, (cuuint32_t)box_rows, (cuuint32_t)box_blocks};
  return make_map(fn, base, 3, dims, strides, box, inner == 64 ? CU_TENSOR_MAP_SWIZZLE_128B : CU_TENSOR_MAP_SWIZZLE_64B);
}

template <typename... KArgs, typename... Args>
void launch(void (*kern)(KArgs...), int grid, int block, int smem, bool pdl, Args... args) {
  cudaLaunchConfig_t cfg = {};
  cfg.gridDim = dim3(grid);
  cfg.blockDim = dim3(block);
  cfg.dynamicSmemBytes = smem;
  cfg.stream = cudaStreamPerThread;
  cudaLaunchAttribute at[1];
  at[0].id = cudaLaunchAttributeProgrammaticStreamSerialization;
  at[0].val.programmaticStreamSerializationAllowed = 1;
  cfg.attrs = at;
  cfg.numAttrs = pdl ? 1 : 0;
  cudaLaunchKernelEx(&cfg, kern, args...);
}

}

extern "C" void kernel_launch(void* const* d_in, const int* in_sizes, int n_in, void* d_out, int out_size) {
  const bf16* x = (const bf16*)d_in[0];
  const bf16* wq = (const bf16*)d_in[1];
  const bf16* wk = (const bf16*)d_in[2];
  const bf16* wv = (const bf16*)d_in[3];
  const bf16* wo = (const bf16*)d_in[4];
  const bf16* w1 = (const bf16*)d_in[6];
  const bf16* w2 = (const bf16*)d_in[7];

  void* fp = nullptr;
  cudaDriverEntryPointQueryResult qr;
  cudaGetDriverEntryPoint("cuTensorMapEncodeTiled", &fp, cudaEnableDefault, &qr);
  EncodeFn fn = (EncodeFn)fp;
  const CUtensorMap mOut = map2d(fn, d_out, S_, D_, 64), mX = map2d(fn, x, S_, D_, 64);
  const CUtensorMap mWq = map3d(fn, wq, D_, D_, 64, 64, 2), mWo = map3d(fn, wo, D_, D_, 64, 64, 2);
  const CUtensorMap mW1 = map3d(fn, w1, D_, F_, 32, 64, 7), mW2 = map3d(fn, w2, F_, D_, 64, 64, 2);

  cudaFuncSetAttribute(qkv_kernel<true>, cudaFuncAttributeMaxDynamicSharedMemorySize, QKV_SMEM);
  cudaFuncSetAttribute(qkv_kernel<false>, cudaFuncAttributeMaxDynamicSharedMemorySize, QKV_SMEM);
  cudaFuncSetAttribute(attn_kernel, cudaFuncAttributeMaxDynamicSharedMemorySize, ATT_SMEM);
  cudaFuncSetAttribute(oproj_kernel, cudaFuncAttributeMaxDynamicSharedMemorySize, OPJ_SMEM);
  cudaFuncSetAttribute(ffn1_kernel, cudaFuncAttributeMaxDynamicSharedMemorySize, F1_SMEM);
  cudaFuncSetAttribute(ffn2_kernel<false>, cudaFuncAttributeMaxDynamicSharedMemorySize, F2_SMEM);
  cudaFuncSetAttribute(ffn2_kernel<true>, cudaFuncAttributeMaxDynamicSharedMemorySize, F2_SMEM);
  void *pX0T, *pX2T;
  cudaGetSymbolAddress(&pX0T, g_x0T);
  cudaGetSymbolAddress(&pX2T, g_x2T);

  for (int layer = 0; layer < 2; layer++) {
    if (layer == 0) launch(qkv_kernel<true>, 128, 256, QKV_SMEM, false, mX, mWq, wk, wv);
    else launch(qkv_kernel<false>, 128, 256, QKV_SMEM, true, mX, mWq, wk, wv);
    launch(attn_kernel, layer == 0 ? 128 + (int)NPACK : 128, 512, ATT_SMEM, true, mW1, wo, w2, 2 + layer * 5);
    launch(oproj_kernel, 128, 192, OPJ_SMEM, true, mWo, (const uint8_t*)(layer == 0 ? pX0T : pX2T), 3 + layer * 5);
    launch(ffn1_kernel, 128, 352, F1_SMEM, true, layer, 4 + layer * 5);
    if (layer == 0) launch(ffn2_kernel<false>, 128, 320, F2_SMEM, true, mW2, mOut, 5 + layer * 5);
    else launch(ffn2_kernel<true>, 128, 320, F2_SMEM, true, mW2, mOut, 5 + layer * 5);
  }
}
```

```cpp
#include <cuda_runtime.h>
#include <cuda_bf16.h>
#include <cuda.h>
#include <stdint.h>

namespace {

typedef __nv_bfloat16 bf16;
constexpr int S_ = 2048, D_ = 512, F_ = 1792;
constexpr float LN_EPS = 1e-5f;
constexpr float QSCALE = 0.25f * 1.4426950408889634f;

constexpr uint32_t LUT_MASK_EVEN = 0x55, LUT_MASK_ODD = 0x5D;
constexpr float SAFE_SCORE_BOUND = 80.0f;

__device__ __align__(1024) uint8_t g_QT[S_ * D_ * 2];
__device__ __align__(1024) uint8_t g_KV[S_ * 64];
__device__ __align__(1024) float g_kmax[32 * 16];
__device__ __align__(1024) uint8_t g_x0T[S_ * D_ * 2];
__device__ __align__(1024) uint8_t g_OT[S_ * D_ * 2];
__device__ __align__(1024) uint8_t g_x1T[S_ * D_ * 2];
__device__ __align__(1024) uint8_t g_x2T[S_ * D_ * 2];
__device__ __align__(1024) uint8_t g_hT[S_ * F_ * 2];
__device__ __align__(1024) float2 g_statA[S_ * 8];
__device__ __align__(1024) float2 g_statB[S_ * 8];
__device__ __align__(1024) float g_csQKV[4 * 136];
__device__ __align__(1024) float g_cs1[F_];
__device__ __align__(1024) uint8_t g_W1p[8 * 8 * 28672];
__device__ unsigned g_pack_done;
constexpr unsigned NPACK = 4;

#define TS(kid, slot)
#define GT(i)
__device__ __forceinline__ uint32_t smem_u32(const void* p) { return (uint32_t)__cvta_generic_to_shared(p); }
__device__ __forceinline__ void mbar_init(uint32_t b, uint32_t c) { asm volatile("mbarrier.init.shared::cta.b64 [%0], %1;" ::"r"(b), "r"(c)); }
__device__ __forceinline__ void mbar_fence_init() { asm volatile("fence.mbarrier_init.release.cluster;" ::: "memory"); }
__device__ __forceinline__ void mbar_expect(uint32_t b, uint32_t bytes) {
  asm volatile("mbarrier.arrive.expect_tx.shared::cta.b64 _, [%0], %1;" ::"r"(b), "r"(bytes) : "memory");
}
__device__ __forceinline__ void mbar_arrive(uint32_t b) { asm volatile("mbarrier.arrive.shared::cta.b64 _, [%0];" ::"r"(b) : "memory"); }
__device__ __forceinline__ void mbar_wait(uint32_t b, uint32_t ph) {
  asm volatile(
      "{.reg .pred p;\n"
      "LAB_WAIT:\n"
      "mbarrier.try_wait.parity.shared::cta.b64 p, [%0], %1;\n"
      "@p bra LAB_DONE;\n"
      "bra LAB_WAIT;\n"
      "LAB_DONE:\n}" ::"r"(b), "r"(ph) : "memory");
}
__device__ __forceinline__ void bulk_g2s(uint32_t dst, const void* src, uint32_t bytes, uint32_t bar) {
  asm volatile("cp.async.bulk.shared::cluster.global.mbarrier::complete_tx::bytes [%0], [%1], %2, [%3];" ::"r"(dst), "l"(src), "r"(bytes), "r"(bar) : "memory");
}
__device__ __forceinline__ void bulk_s2g(void* dst, uint32_t src, uint32_t bytes) {
  asm volatile("cp.async.bulk.global.shared::cta.bulk_group [%0], [%1], %2;" ::"l"(dst), "r"(src), "r"(bytes) : "memory");
}
__device__ __forceinline__ bool pack_ready() {
  unsigned v;
  asm volatile("ld.acquire.gpu.global.u32 %0, [%1];" : "=r"(v) : "l"(&g_pack_done) : "memory");
  return v == NPACK;
}
__device__ __forceinline__ void tma2d(uint32_t dst, const CUtensorMap* m, int c0, int c1, uint32_t bar) {
  asm volatile("cp.async.bulk.tensor.2d.shared::cluster.global.mbarrier::complete_tx::bytes [%0], [%1, {%3, %4}], [%2];"
               ::"r"(dst), "l"(m), "r"(bar), "r"(c0), "r"(c1) : "memory");
}
__device__ __forceinline__ void tma3d(uint32_t dst, const CUtensorMap* m, int c0, int c1, int c2, uint32_t bar) {
  asm volatile("cp.async.bulk.tensor.3d.shared::cluster.global.mbarrier::complete_tx::bytes [%0], [%1, {%3, %4, %5}], [%2];"
               ::"r"(dst), "l"(m), "r"(bar), "r"(c0), "r"(c1), "r"(c2) : "memory");
}
__device__ __forceinline__ void tmap_prefetch(const CUtensorMap* m) { asm volatile("prefetch.tensormap [%0];" ::"l"(m) : "memory"); }
__device__ __forceinline__ void tma2d_store(const CUtensorMap* m, int c0, int c1, uint32_t src) {
  asm volatile("cp.async.bulk.tensor.2d.global.shared::cta.bulk_group [%0, {%2, %3}], [%1];" ::"l"(m), "r"(src), "r"(c0), "r"(c1) : "memory");
}
__device__ __forceinline__ void bulk_commit_wait_all() {
  asm volatile("cp.async.bulk.commit_group;" ::: "memory");
  asm volatile("cp.async.bulk.wait_group 0;" ::: "memory");
}
__device__ __forceinline__ void fence_async_smem() { asm volatile("fence.proxy.async.shared::cta;" ::: "memory"); }
__device__ __forceinline__ void pdl_trigger() { asm volatile("griddepcontrol.launch_dependents;" ::: "memory"); }
__device__ __forceinline__ void pdl_wait() { asm volatile("griddepcontrol.wait;" ::: "memory"); }
__device__ __forceinline__ void bar_sync(int id, int n) { asm volatile("bar.sync %0, %1;" ::"r"(id), "r"(n) : "memory"); }
__device__ __forceinline__ void wg_fence() { asm volatile("wgmma.fence.sync.aligned;" ::: "memory"); }
__device__ __forceinline__ void wg_commit() { asm volatile("wgmma.commit_group.sync.aligned;" ::: "memory"); }
template <int N> __device__ __forceinline__ void wg_wait() { asm volatile("wgmma.wait_group.sync.aligned %0;" ::"n"(N) : "memory"); }
__device__ __forceinline__ uint64_t mkdesc(uint32_t addr, uint32_t lbo, uint32_t sbo, uint32_t swz) {
  return (uint64_t)((addr & 0x3FFFF) >> 4) | ((uint64_t)(lbo >> 4) << 16) | ((uint64_t)(sbo >> 4) << 32) | ((uint64_t)swz << 62);
}
template <int N> __device__ __forceinline__ void fence_regs(float* d) {
#pragma unroll
  for (int i = 0; i < N; i++) asm volatile("" : "+f"(d[i])::"memory");
}
template <int N> __device__ __forceinline__ void fence_regs_u(uint32_t* d) {
#pragma unroll
  for (int i = 0; i < N; i++) asm volatile("" : "+r"(d[i])::"memory");
}
__device__ __forceinline__ uint32_t pack_bf16(float lo, float hi) {
  uint32_t r;
  asm("cvt.rn.bf16x2.f32 %0, %1, %2;" : "=r"(r) : "f"(hi), "f"(lo));
  return r;
}
__device__ __forceinline__ float bf_lo(uint32_t u) { return __uint_as_float(u << 16); }
__device__ __forceinline__ float bf_hi(uint32_t u) { return __uint_as_float(u & 0xFFFF0000u); }
__device__ __forceinline__ float ex2f(float x) {
  float y;
  asm("ex2.approx.ftz.f32 %0, %1;" : "=f"(y) : "f"(x));
  return y;
}
__device__ __forceinline__ void stsm4(uint32_t a, uint32_t r0, uint32_t r1, uint32_t r2, uint32_t r3) {
  asm volatile("stmatrix.sync.aligned.m8n8.x4.shared.b16 [%0], {%1,%2,%3,%4};" ::"r"(a), "r"(r0), "r"(r1), "r"(r2), "r"(r3) : "memory");
}
__device__ __forceinline__ void ldsm4(uint32_t* r, uint32_t a) {
  asm volatile("ldmatrix.sync.aligned.m8n8.x4.shared.b16 {%0,%1,%2,%3}, [%4];" : "=r"(r[0]), "=r"(r[1]), "=r"(r[2]), "=r"(r[3]) : "r"(a) : "memory");
}
__device__ __forceinline__ void ldsm4t(uint32_t* r, uint32_t a) {
  asm volatile("ldmatrix.sync.aligned.m8n8.x4.trans.shared.b16 {%0,%1,%2,%3}, [%4];" : "=r"(r[0]), "=r"(r[1]), "=r"(r[2]), "=r"(r[3]) : "r"(a) : "memory");
}
__device__ __forceinline__ void mma16816(float* d, const uint32_t* a, uint32_t b0, uint32_t b1) {
  asm volatile("mma.sync.aligned.m16n8k16.row.col.f32.bf16.bf16.f32 {%0,%1,%2,%3}, {%4,%5,%6,%7}, {%8,%9}, {%0,%1,%2,%3};"
               : "+f"(d[0]), "+f"(d[1]), "+f"(d[2]), "+f"(d[3]) : "r"(a[0]), "r"(a[1]), "r"(a[2]), "r"(a[3]), "r"(b0), "r"(b1));
}
__device__ __forceinline__ void row_stats(const float2* __restrict__ st, int row, float& mean, float& rstd) {
  const float4* p = reinterpret_cast<const float4*>(st + row * 8);
  float s = 0.f, q = 0.f;
#pragma unroll
  for (int i = 0; i < 4; i++) {
    float4 v = __ldcg(p + i);
    s += v.x + v.z;
    q += v.y + v.w;
  }
  mean = s * (1.f / D_);
  float var = fmaxf(q * (1.f / D_) - mean * mean, 0.f);
  rstd = rsqrtf(var + LN_EPS);
}

__device__ __forceinline__ void wgmma_rs_n64(float* d, uint32_t a0, uint32_t a1, uint32_t a2, uint32_t a3, uint64_t descB, int scaleD){
  asm volatile("{.reg .pred p; setp.ne.b32 p, %37, 0; wgmma.mma_async.sync.aligned.m64n64k16.f32.bf16.bf16 {%0,%1,%2,%3,%4,%5,%6,%7,%8,%9,%10,%11,%12,%13,%14,%15,%16,%17,%18,%19,%20,%21,%22,%23,%24,%25,%26,%27,%28,%29,%30,%31}, {%32,%33,%34,%35}, %36, p, 1, 1, 0;}"
   : "+f"(d[0]),"+f"(d[1]),"+f"(d[2]),"+f"(d[3]),"+f"(d[4]),"+f"(d[5]),"+f"(d[6]),"+f"(d[7]),"+f"(d[8]),"+f"(d[9]),"+f"(d[10]),"+f"(d[11]),"+f"(d[12]),"+f"(d[13]),"+f"(d[14]),"+f"(d[15]),"+f"(d[16]),"+f"(d[17]),"+f"(d[18]),"+f"(d[19]),"+f"(d[20]),"+f"(d[21]),"+f"(d[22]),"+f"(d[23]),"+f"(d[24]),"+f"(d[25]),"+f"(d[26]),"+f"(d[27]),"+f"(d[28]),"+f"(d[29]),"+f"(d[30]),"+f"(d[31])
   : "r"(a0),"r"(a1),"r"(a2),"r"(a3),"l"(descB),"r"(scaleD));
}

__device__ __forceinline__ void wgmma_rs_tb_n24(float* d, uint32_t a0, uint32_t a1, uint32_t a2, uint32_t a3, uint64_t descB, int scaleD){
  asm volatile("{.reg .pred p; setp.ne.b32 p, %17, 0; wgmma.mma_async.sync.aligned.m64n24k16.f32.bf16.bf16 {%0,%1,%2,%3,%4,%5,%6,%7,%8,%9,%10,%11}, {%12,%13,%14,%15}, %16, p, 1, 1, 1;}"
   : "+f"(d[0]),"+f"(d[1]),"+f"(d[2]),"+f"(d[3]),"+f"(d[4]),"+f"(d[5]),"+f"(d[6]),"+f"(d[7]),"+f"(d[8]),"+f"(d[9]),"+f"(d[10]),"+f"(d[11])
   : "r"(a0),"r"(a1),"r"(a2),"r"(a3),"l"(descB),"r"(scaleD));
}

__device__ __forceinline__ void wgmma_ss_tb_n128(float* d, uint64_t descA, uint64_t descB, int scaleD){
  asm volatile("{.reg .pred p; setp.ne.b32 p, %66, 0; wgmma.mma_async.sync.aligned.m64n128k16.f32.bf16.bf16 {%0,%1,%2,%3,%4,%5,%6,%7,%8,%9,%10,%11,%12,%13,%14,%15,%16,%17,%18,%19,%20,%21,%22,%23,%24,%25,%26,%27,%28,%29,%30,%31,%32,%33,%34,%35,%36,%37,%38,%39,%40,%41,%42,%43,%44,%45,%46,%47,%48,%49,%50,%51,%52,%53,%54,%55,%56,%57,%58,%59,%60,%61,%62,%63}, %64, %65, p, 1, 1, 0, 1;}"
   : "+f"(d[0]),"+f"(d[1]),"+f"(d[2]),"+f"(d[3]),"+f"(d[4]),"+f"(d[5]),"+f"(d[6]),"+f"(d[7]),"+f"(d[8]),"+f"(d[9]),"+f"(d[10]),"+f"(d[11]),"+f"(d[12]),"+f"(d[13]),"+f"(d[14]),"+f"(d[15]),"+f"(d[16]),"+f"(d[17]),"+f"(d[18]),"+f"(d[19]),"+f"(d[20]),"+f"(d[21]),"+f"(d[22]),"+f"(d[23]),"+f"(d[24]),"+f"(d[25]),"+f"(d[26]),"+f"(d[27]),"+f"(d[28]),"+f"(d[29]),"+f"(d[30]),"+f"(d[31]),"+f"(d[32]),"+f"(d[33]),"+f"(d[34]),"+f"(d[35]),"+f"(d[36]),"+f"(d[37]),"+f"(d[38]),"+f"(d[39]),"+f"(d[40]),"+f"(d[41]),"+f"(d[42]),"+f"(d[43]),"+f"(d[44]),"+f"(d[45]),"+f"(d[46]),"+f"(d[47]),"+f"(d[48]),"+f"(d[49]),"+f"(d[50]),"+f"(d[51]),"+f"(d[52]),"+f"(d[53]),"+f"(d[54]),"+f"(d[55]),"+f"(d[56]),"+f"(d[57]),"+f"(d[58]),"+f"(d[59]),"+f"(d[60]),"+f"(d[61]),"+f"(d[62]),"+f"(d[63])
   : "l"(descA),"l"(descB),"r"(scaleD));
}

__device__ __forceinline__ void wgmma_ss_tb_n136(float* d, uint64_t descA, uint64_t descB, int scaleD){
  asm volatile("{.reg .pred p; setp.ne.b32 p, %70, 0; wgmma.mma_async.sync.aligned.m64n136k16.f32.bf16.bf16 {%0,%1,%2,%3,%4,%5,%6,%7,%8,%9,%10,%11,%12,%13,%14,%15,%16,%17,%18,%19,%20,%21,%22,%23,%24,%25,%26,%27,%28,%29,%30,%31,%32,%33,%34,%35,%36,%37,%38,%39,%40,%41,%42,%43,%44,%45,%46,%47,%48,%49,%50,%51,%52,%53,%54,%55,%56,%57,%58,%59,%60,%61,%62,%63,%64,%65,%66,%67}, %68, %69, p, 1, 1, 0, 1;}"
   : "+f"(d[0]),"+f"(d[1]),"+f"(d[2]),"+f"(d[3]),"+f"(d[4]),"+f"(d[5]),"+f"(d[6]),"+f"(d[7]),"+f"(d[8]),"+f"(d[9]),"+f"(d[10]),"+f"(d[11]),"+f"(d[12]),"+f"(d[13]),"+f"(d[14]),"+f"(d[15]),"+f"(d[16]),"+f"(d[17]),"+f"(d[18]),"+f"(d[19]),"+f"(d[20]),"+f"(d[21]),"+f"(d[22]),"+f"(d[23]),"+f"(d[24]),"+f"(d[25]),"+f"(d[26]),"+f"(d[27]),"+f"(d[28]),"+f"(d[29]),"+f"(d[30]),"+f"(d[31]),"+f"(d[32]),"+f"(d[33]),"+f"(d[34]),"+f"(d[35]),"+f"(d[36]),"+f"(d[37]),"+f"(d[38]),"+f"(d[39]),"+f"(d[40]),"+f"(d[41]),"+f"(d[42]),"+f"(d[43]),"+f"(d[44]),"+f"(d[45]),"+f"(d[46]),"+f"(d[47]),"+f"(d[48]),"+f"(d[49]),"+f"(d[50]),"+f"(d[51]),"+f"(d[52]),"+f"(d[53]),"+f"(d[54]),"+f"(d[55]),"+f"(d[56]),"+f"(d[57]),"+f"(d[58]),"+f"(d[59]),"+f"(d[60]),"+f"(d[61]),"+f"(d[62]),"+f"(d[63]),"+f"(d[64]),"+f"(d[65]),"+f"(d[66]),"+f"(d[67])
   : "l"(descA),"l"(descB),"r"(scaleD));
}

__device__ __forceinline__ void wgmma_ss_tb_n224(float* d, uint64_t descA, uint64_t descB, int scaleD){
  asm volatile("{.reg .pred p; setp.ne.b32 p, %114, 0; wgmma.mma_async.sync.aligned.m64n224k16.f32.bf16.bf16 {%0,%1,%2,%3,%4,%5,%6,%7,%8,%9,%10,%11,%12,%13,%14,%15,%16,%17,%18,%19,%20,%21,%22,%23,%24,%25,%26,%27,%28,%29,%30,%31,%32,%33,%34,%35,%36,%37,%38,%39,%40,%41,%42,%43,%44,%45,%46,%47,%48,%49,%50,%51,%52,%53,%54,%55,%56,%57,%58,%59,%60,%61,%62,%63,%64,%65,%66,%67,%68,%69,%70,%71,%72,%73,%74,%75,%76,%77,%78,%79,%80,%81,%82,%83,%84,%85,%86,%87,%88,%89,%90,%91,%92,%93,%94,%95,%96,%97,%98,%99,%100,%101,%102,%103,%104,%105,%106,%107,%108,%109,%110,%111}, %112, %113, p, 1, 1, 0, 1;}"
   : "+f"(d[0]),"+f"(d[1]),"+f"(d[2]),"+f"(d[3]),"+f"(d[4]),"+f"(d[5]),"+f"(d[6]),"+f"(d[7]),"+f"(d[8]),"+f"(d[9]),"+f"(d[10]),"+f"(d[11]),"+f"(d[12]),"+f"(d[13]),"+f"(d[14]),"+f"(d[15]),"+f"(d[16]),"+f"(d[17]),"+f"(d[18]),"+f"(d[19]),"+f"(d[20]),"+f"(d[21]),"+f"(d[22]),"+f"(d[23]),"+f"(d[24]),"+f"(d[25]),"+f"(d[26]),"+f"(d[27]),"+f"(d[28]),"+f"(d[29]),"+f"(d[30]),"+f"(d[31]),"+f"(d[32]),"+f"(d[33]),"+f"(d[34]),"+f"(d[35]),"+f"(d[36]),"+f"(d[37]),"+f"(d[38]),"+f"(d[39]),"+f"(d[40]),"+f"(d[41]),"+f"(d[42]),"+f"(d[43]),"+f"(d[44]),"+f"(d[45]),"+f"(d[46]),"+f"(d[47]),"+f"(d[48]),"+f"(d[49]),"+f"(d[50]),"+f"(d[51]),"+f"(d[52]),"+f"(d[53]),"+f"(d[54]),"+f"(d[55]),"+f"(d[56]),"+f"(d[57]),"+f"(d[58]),"+f"(d[59]),"+f"(d[60]),"+f"(d[61]),"+f"(d[62]),"+f"(d[63]),"+f"(d[64]),"+f"(d[65]),"+f"(d[66]),"+f"(d[67]),"+f"(d[68]),"+f"(d[69]),"+f"(d[70]),"+f"(d[71]),"+f"(d[72]),"+f"(d[73]),"+f"(d[74]),"+f"(d[75]),"+f"(d[76]),"+f"(d[77]),"+f"(d[78]),"+f"(d[79]),"+f"(d[80]),"+f"(d[81]),"+f"(d[82]),"+f"(d[83]),"+f"(d[84]),"+f"(d[85]),"+f"(d[86]),"+f"(d[87]),"+f"(d[88]),"+f"(d[89]),"+f"(d[90]),"+f"(d[91]),"+f"(d[92]),"+f"(d[93]),"+f"(d[94]),"+f"(d[95]),"+f"(d[96]),"+f"(d[97]),"+f"(d[98]),"+f"(d[99]),"+f"(d[100]),"+f"(d[101]),"+f"(d[102]),"+f"(d[103]),"+f"(d[104]),"+f"(d[105]),"+f"(d[106]),"+f"(d[107]),"+f"(d[108]),"+f"(d[109]),"+f"(d[110]),"+f"(d[111])
   : "l"(descA),"l"(descB),"r"(scaleD));
}

constexpr int QKV_CH = 8192 + 16384;
constexpr int QKV_KV = 8 * QKV_CH;
constexpr int QKV_AUX = QKV_KV + 8192;
constexpr int QKV_SMEM = QKV_AUX + 2048 + 1024;

template <bool FIRST>
__global__ void __launch_bounds__(256, 1) qkv_kernel(const __grid_constant__ CUtensorMap mX, const __grid_constant__ CUtensorMap mWq,
                                                      const bf16* __restrict__ wk, const bf16* __restrict__ wv) {
  extern __shared__ uint8_t smraw[];
  const uint32_t sb = (smem_u32(smraw) + 1023) & ~1023u;
  uint8_t* sp = smraw + (sb - smem_u32(smraw));
  float* s_mean = reinterpret_cast<float*>(sp + QKV_AUX);
  float* s_rstd = s_mean + 64;
  float* s_cs = s_rstd + 64;
  float* s_km = s_cs + 128;
  const uint32_t bars = sb + QKV_AUX + 1536;
  const int tid = threadIdx.x, lane = tid & 31, warp = tid >> 5;
  const int tb = blockIdx.x >> 2, hg = blockIdx.x & 3;
  const int KID = FIRST ? 1 : 6;
  if (tid == 0) TS(KID, 0);
  if (FIRST && tid == 0 && blockIdx.x == 0) GT(0);
  pdl_trigger();
  if (tid == 0) {
    tmap_prefetch(&mWq);
    if (FIRST) tmap_prefetch(&mX);
    for (int i = 0; i < 8; i++) mbar_init(bars + i * 8, 1);
    mbar_fence_init();
  }
  __syncthreads();
  if (tid == 128) {
#pragma unroll 1
    for (int kc = 0; kc < 8; kc++) {
      mbar_expect(bars + kc * 8, QKV_CH);
      tma3d(sb + kc * QKV_CH + 8192, &mWq, 0, kc * 64, hg * 2, bars + kc * 8);
    }
  } else if (tid == 160) {
    if (!FIRST) { TS(KID, 6); pdl_wait(); TS(KID, 5); }
#pragma unroll 1
    for (int kc = 0; kc < 8; kc++) {
      if (FIRST) tma2d(sb + kc * QKV_CH, &mX, kc * 64, tb * 64, bars + kc * 8);
      else bulk_g2s(sb + kc * QKV_CH, g_x2T + (tb * 8 + kc) * 8192, 8192, bars + kc * 8);
    }
  }
  __syncwarp();
  const int g = lane >> 2, t = lane & 3;
  if (warp >= 4) {
    const int t1 = tid & 127, w4 = warp & 3;
    const bf16* wkv = (hg < 2 ? wk : wv) + (hg & 1) * 8;
    {
      uint4 v[4];
#pragma unroll
      for (int i = 0; i < 4; i++) v[i] = __ldg(reinterpret_cast<const uint4*>(wkv + (size_t)(i * 128 + t1) * 16));
#pragma unroll
      for (int i = 0; i < 4; i++) *reinterpret_cast<uint4*>(sp + QKV_KV + (i * 128 + t1) * 16) = v[i];
    }
    float mean0, rstd0, mean1, rstd1;
    const int rl0 = w4 * 16 + g, r0 = tb * 64 + rl0;
    if (!FIRST) {
      pdl_wait();
      row_stats(g_statA, r0, mean0, rstd0);
      row_stats(g_statA, r0 + 8, mean1, rstd1);
      s_cs[t1] = __ldcg(g_csQKV + hg * 136 + t1);
    }
    bar_sync(2, 128);
    float kv[4] = {0.f, 0.f, 0.f, 0.f}, ones[4] = {0.f, 0.f, 0.f, 0.f}, cs[8];
    float rs0 = 0.f, rq0 = 0.f, rs1 = 0.f, rq1 = 0.f;
#pragma unroll
    for (int i = 0; i < 8; i++) cs[i] = 0.f;
    const int arow = w4 * 16 + (lane & 15);
#pragma unroll 1
    for (int kc = 0; kc < 8; kc++) {
      mbar_wait(bars + kc * 8, 0);
      const uint32_t st = sb + kc * QKV_CH;
#pragma unroll
      for (int ks = 0; ks < 4; ks++) {
        uint32_t a[4], b[4];
        ldsm4(a, st + arow * 128 + (((ks * 2 + (lane >> 4)) ^ (arow & 7)) << 4));
        ldsm4t(b, sb + QKV_KV + (kc * 64 + ks * 16 + (lane & 15)) * 16);
        mma16816(kv, a, b[0], b[1]);
        if (FIRST) {
          const float f0 = bf_lo(a[0]), f1 = bf_hi(a[0]), f2 = bf_lo(a[2]), f3 = bf_hi(a[2]);
          const float h0 = bf_lo(a[1]), h1 = bf_hi(a[1]), h2 = bf_lo(a[3]), h3 = bf_hi(a[3]);
          rs0 += (f0 + f1) + (f2 + f3); rq0 += f0 * f0 + f1 * f1 + f2 * f2 + f3 * f3;
          rs1 += (h0 + h1) + (h2 + h3); rq1 += h0 * h0 + h1 * h1 + h2 * h2 + h3 * h3;
          const uint32_t one[4] = {0x3F803F80u, 0x3F803F80u, 0x3F803F80u, 0x3F803F80u};
          mma16816(ones, one, b[0], b[1]);
        }
      }
      if (FIRST) {
        const int cg = t1 >> 3, kr = t1 & 7;
        const uint8_t* bp = sp + kc * QKV_CH + 8192 + (cg >> 3) * 8192 + kr * 128 + (((cg & 7) ^ kr) << 4);
#pragma unroll
        for (int kg = 0; kg < 8; kg++) {
          const uint4 v = *reinterpret_cast<const uint4*>(bp + kg * 1024);
          cs[0] += bf_lo(v.x); cs[1] += bf_hi(v.x); cs[2] += bf_lo(v.y); cs[3] += bf_hi(v.y);
          cs[4] += bf_lo(v.z); cs[5] += bf_hi(v.z); cs[6] += bf_lo(v.w); cs[7] += bf_hi(v.w);
        }
      }
    }
    float ck0, ck1;
    if (FIRST) {
#pragma unroll
      for (int o = 1; o < 4; o <<= 1) {
        rs0 += __shfl_xor_sync(~0u, rs0, o); rq0 += __shfl_xor_sync(~0u, rq0, o);
        rs1 += __shfl_xor_sync(~0u, rs1, o); rq1 += __shfl_xor_sync(~0u, rq1, o);
      }
      mean0 = rs0 * (1.f / D_); mean1 = rs1 * (1.f / D_);
      rstd0 = rsqrtf(fmaxf(rq0 * (1.f / D_) - mean0 * mean0, 0.f) + LN_EPS);
      rstd1 = rsqrtf(fmaxf(rq1 * (1.f / D_) - mean1 * mean1, 0.f) + LN_EPS);
#pragma unroll
      for (int i = 0; i < 8; i++) {
#pragma unroll
        for (int o = 1; o < 8; o <<= 1) cs[i] += __shfl_xor_sync(~0u, cs[i], o);
      }
      if ((t1 & 7) == 0) {
#pragma unroll
        for (int i = 0; i < 8; i++) s_cs[(t1 >> 3) * 8 + i] = cs[i];
        if (tb == 0) {
#pragma unroll
          for (int i = 0; i < 8; i++) g_csQKV[hg * 136 + (t1 >> 3) * 8 + i] = cs[i];
        }
      }
      ck0 = ones[0]; ck1 = ones[1];
      if (tb == 0 && w4 == 0 && g == 0) { g_csQKV[hg * 136 + 128 + 2 * t] = ck0; g_csQKV[hg * 136 + 128 + 2 * t + 1] = ck1; }
      if (hg == 0 && t1 == 0) {
#pragma unroll 1
        for (int kc = 0; kc < 8; kc++) bulk_s2g(g_x0T + (tb * 8 + kc) * 8192, sb + kc * QKV_CH, 8192);
        asm volatile("cp.async.bulk.commit_group;" ::: "memory");
      }
    } else {
      ck0 = __ldcg(g_csQKV + hg * 136 + 128 + 2 * t);
      ck1 = __ldcg(g_csQKV + hg * 136 + 128 + 2 * t + 1);
    }
    if (t == 0) { s_mean[rl0] = mean0; s_rstd[rl0] = rstd0; s_mean[rl0 + 8] = mean1; s_rstd[rl0 + 8] = rstd1; }
    asm volatile("bar.arrive 1, 256;" ::: "memory");
    uint32_t u0 = pack_bf16((kv[0] - mean0 * ck0) * rstd0, (kv[1] - mean0 * ck1) * rstd0);
    uint32_t u1 = pack_bf16((kv[2] - mean1 * ck0) * rstd1, (kv[3] - mean1 * ck1) * rstd1);
    uint8_t* kvp = g_KV + (r0 >> 8) * 16384;
    const int kk = r0 & 255;
    if (hg < 2) {
      *reinterpret_cast<uint32_t*>(kvp + (kk >> 3) * 256 + hg * 128 + (kk & 7) * 16 + t * 4) = u0;
      *reinterpret_cast<uint32_t*>(kvp + ((kk + 8) >> 3) * 256 + hg * 128 + (kk & 7) * 16 + t * 4) = u1;
      float m0 = fmaxf(fabsf(bf_lo(u0)), fabsf(bf_lo(u1))), m1 = fmaxf(fabsf(bf_hi(u0)), fabsf(bf_hi(u1)));
      if (!(bf_lo(u0) == bf_lo(u0)) || !(bf_lo(u1) == bf_lo(u1))) m0 = __int_as_float(0x7f800000);
      if (!(bf_hi(u0) == bf_hi(u0)) || !(bf_hi(u1) == bf_hi(u1))) m1 = __int_as_float(0x7f800000);
#pragma unroll
      for (int o = 4; o < 32; o <<= 1) { m0 = fmaxf(m0, __shfl_xor_sync(~0u, m0, o)); m1 = fmaxf(m1, __shfl_xor_sync(~0u, m1, o)); }
      if (g == 0) { s_km[w4 * 8 + 2 * t] = m0; s_km[w4 * 8 + 2 * t + 1] = m1; }
      bar_sync(2, 128);
      if (t1 < 8) g_kmax[tb * 16 + hg * 8 + t1] = fmaxf(fmaxf(s_km[t1], s_km[8 + t1]), fmaxf(s_km[16 + t1], s_km[24 + t1]));
    } else {
      const uint32_t mask = ((r0 >> 6) & 1) ? LUT_MASK_ODD : LUT_MASK_EVEN;
      if ((mask >> ((r0 >> 3) & 7)) & 1) u0 ^= 0x80008000u;
      if ((mask >> (((r0 + 8) >> 3) & 7)) & 1) u1 ^= 0x80008000u;
      *reinterpret_cast<uint32_t*>(kvp + 8192 + (hg - 2) * 4096 + kk * 16 + t * 4) = u0;
      *reinterpret_cast<uint32_t*>(kvp + 8192 + (hg - 2) * 4096 + (kk + 8) * 16 + t * 4) = u1;
    }
    if (FIRST && hg == 0 && t1 == 0) asm volatile("cp.async.bulk.wait_group 0;" ::: "memory");
    return;
  }
  float acc[64];
#pragma unroll
  for (int i = 0; i < 64; i++) acc[i] = 0.f;
  fence_regs<64>(acc);
#pragma unroll 1
  for (int kc = 0; kc < 8; kc++) {
    const uint32_t st = sb + kc * QKV_CH;
    mbar_wait(bars + kc * 8, 0);
    if (tid == 0 && kc == 0) TS(KID, 1);
    wg_fence();
#pragma unroll
    for (int ks = 0; ks < 4; ks++)
      wgmma_ss_tb_n128(acc, mkdesc(st + ks * 32, 16, 1024, 1), mkdesc(st + 8192 + ks * 2048, 8192, 1024, 1), 1);
    wg_commit();
  }
  wg_wait<0>();
  fence_regs<64>(acc);
  if (tid == 0) TS(KID, 2);
  bar_sync(1, 256);
  if (!FIRST) pdl_wait();
  if (tid == 0) TS(KID, 4);
  const int rl0 = warp * 16 + g;
  const float mean0 = s_mean[rl0], mean1 = s_mean[rl0 + 8];
  const float q0 = s_rstd[rl0] * QSCALE, q1 = s_rstd[rl0 + 8] * QSCALE;
  const uint32_t stg = sb + 8192;
  const int rl = warp * 16 + ((lane >> 3) & 1) * 8 + (lane & 7);
#pragma unroll
  for (int j = 0; j < 16; j += 2) {
    const float2 ca = *reinterpret_cast<const float2*>(s_cs + 8 * j + 2 * t);
    const float2 cb = *reinterpret_cast<const float2*>(s_cs + 8 * j + 8 + 2 * t);
    const float* a = acc + 4 * j;
    stsm4(stg + (j >> 3) * 8192 + rl * 128 + ((((j & 7) + (lane >> 4)) ^ (rl & 7)) << 4),
          pack_bf16((a[0] - mean0 * ca.x) * q0, (a[1] - mean0 * ca.y) * q0), pack_bf16((a[2] - mean1 * ca.x) * q1, (a[3] - mean1 * ca.y) * q1),
          pack_bf16((a[4] - mean0 * cb.x) * q0, (a[5] - mean0 * cb.y) * q0), pack_bf16((a[6] - mean1 * cb.x) * q1, (a[7] - mean1 * cb.y) * q1));
  }
  fence_async_smem();
  bar_sync(3, 128);
  if (tid == 0) {
    bulk_s2g(g_QT + (tb * 8 + hg * 2) * 8192, stg, 16384);
    bulk_commit_wait_all();
    TS(KID, 3);
  }
}

constexpr int ATT_SMEM = 31 * 1024 + 192 * 1024 + 2048 + 1024;
constexpr int KVCH = 20480;
constexpr float LUT_MAGIC = 382.875f;

template <uint32_t MASK>
__device__ __forceinline__ void exp_pack(const float* s, uint32_t* p, uint32_t lutlane) {
#pragma unroll
  for (int i = 0; i < 16; i++) {
    if ((MASK >> (i / 2)) & 1) {
      const uint32_t b0 = __float_as_uint(s[2 * i] + LUT_MAGIC), b1 = __float_as_uint(s[2 * i + 1] + LUT_MAGIC);
      uint32_t c0, c1, w;
      asm volatile("ld.shared.u16 %0, [%1+2];" : "=r"(c0) : "r"((b0 & 0x7F80u) | lutlane));
      asm volatile("ld.shared.u32 %0, [%1];" : "=r"(c1) : "r"((b1 & 0x7F80u) | lutlane));
      asm("prmt.b32 %0, %1, %2, 0x6521;" : "=r"(w) : "r"(b0), "r"(b1));
      p[i] = w + c0 + c1;
    } else {
      p[i] = pack_bf16(ex2f(s[2 * i]), ex2f(s[2 * i + 1]));
    }
  }
}

__device__ __noinline__ void pack_weights(const CUtensorMap* mW1, const bf16* __restrict__ wo, const bf16* __restrict__ w2, int cta, uint8_t* smraw) {
  const int tid = threadIdx.x;
  const uint32_t sb = (smem_u32(smraw) + 1023) & ~1023u;
  uint8_t* sp = smraw + (sb - smem_u32(smraw));
  constexpr int IMG = 28672, NBUF = 7;
  const uint32_t bars = sb + NBUF * IMG;
  float* part = reinterpret_cast<float*>(sp + NBUF * IMG + 64);
  if (tid == 0) {
    for (int i = 0; i < NBUF; i++) mbar_init(bars + i * 8, 1);
    mbar_fence_init();
    for (int i = 0; i < NBUF; i++) { mbar_expect(bars + i * 8, IMG); tma3d(sb + i * IMG, mW1, 0, (i & 7) * 64, (cta * 2 + (i >> 3)) * 7, bars + i * 8); }
  }
  if (tid == 32) {
    constexpr uint32_t WO_B = D_ * D_ * 2 / NPACK, W2_B = F_ * D_ * 2 / NPACK;
    for (uint32_t o = 0; o < WO_B; o += 16384) asm volatile("cp.async.bulk.prefetch.L2.global [%0], %1;" ::"l"((const char*)wo + cta * WO_B + o), "r"(16384));
    for (uint32_t o = 0; o < W2_B; o += 16384) asm volatile("cp.async.bulk.prefetch.L2.global [%0], %1;" ::"l"((const char*)w2 + cta * W2_B + o), "r"(16384));
  }
  __syncthreads();
  const int cg = tid % 28, rg = tid / 28;
  float cs[8];
#pragma unroll
  for (int i = 0; i < 8; i++) cs[i] = 0.f;
#pragma unroll 1
  for (int it = 0; it < 16; it++) {
    const int buf = it % NBUF;
    mbar_wait(bars + buf * 8, (it / NBUF) & 1);
    if (tid == 0) { bulk_s2g(g_W1p + (size_t)(cta * 16 + it) * IMG, sb + buf * IMG, IMG); asm volatile("cp.async.bulk.commit_group;" ::: "memory"); }
    if (tid < 448) {
#pragma unroll
      for (int r = 0; r < 4; r++) {
        const int row = rg * 4 + r;
        const uint4 v = *reinterpret_cast<const uint4*>(sp + buf * IMG + (cg >> 2) * 4096 + row * 64 + (((cg & 3) ^ ((row >> 1) & 3)) << 4));
        cs[0] += bf_lo(v.x); cs[1] += bf_hi(v.x); cs[2] += bf_lo(v.y); cs[3] += bf_hi(v.y);
        cs[4] += bf_lo(v.z); cs[5] += bf_hi(v.z); cs[6] += bf_lo(v.w); cs[7] += bf_hi(v.w);
      }
    }
    if ((it & 7) == 7) {
      if (tid < 448) {
#pragma unroll
        for (int i = 0; i < 8; i++) { part[rg * 224 + cg * 8 + i] = cs[i]; cs[i] = 0.f; }
      }
      __syncthreads();
      if (tid < 224) {
        float s = 0.f;
#pragma unroll
        for (int q = 0; q < 16; q++) s += part[q * 224 + tid];
        g_cs1[(cta * 2 + (it >> 3)) * 224 + tid] = s;
      }
    }
    __syncthreads();
    if (tid == 0 && it + NBUF < 16) {
      asm volatile("cp.async.bulk.wait_group.read 0;" ::: "memory");
      const int nx = it + NBUF;
      mbar_expect(bars + buf * 8, IMG);
      tma3d(sb + buf * IMG, mW1, 0, (nx & 7) * 64, (cta * 2 + (nx >> 3)) * 7, bars + buf * 8);
    }
  }
  if (tid == 0) asm volatile("cp.async.bulk.wait_group 0;" ::: "memory");
  __threadfence();
  __syncthreads();
  if (tid == 0) asm volatile("red.release.gpu.global.add.u32 [%0], 1;" ::"l"(&g_pack_done) : "memory");
}

__global__ void __launch_bounds__(512, 1) attn_kernel(const __grid_constant__ CUtensorMap mW1, const bf16* __restrict__ wo, const bf16* __restrict__ w2, int KID) {
  extern __shared__ uint8_t smraw[];
  const uint32_t sbase = smem_u32(smraw);
  const uint32_t bars = sbase;
  const uint32_t kred = sbase + 128;
  const uint32_t qst = (sbase + 4096 + 1023) & ~1023u;
  const uint32_t LUT = (qst + 16384 + 32767) & ~32767u;
  const uint32_t KS = LUT + 32768;
  if (blockIdx.x >= 128) { pdl_trigger(); pack_weights(&mW1, wo, w2, blockIdx.x - 128, smraw); return; }
  uint8_t* sm0 = smraw - sbase;
  const int tid = threadIdx.x, lane = tid & 31, wg = tid >> 7, warp = (tid >> 5) & 3;
  if (tid == 0) TS(KID, 0);
  pdl_trigger();
  if (tid == 0) {
    for (int i = 0; i < 8; i++) mbar_init(bars + i * 8, 1);
    mbar_fence_init();
  }
  for (int i = tid; i < 256 * 32; i += 512) {
    const int idx = i >> 5;
    const float v = exp2f((idx + 0.5f) * (1.f / 256.f) + 0.125f);
    const int target = (v < 2.f) ? (int)rintf(128.f * v) - 128 : (int)rintf(64.f * v);
    reinterpret_cast<uint32_t*>(sm0 + LUT)[i] = (uint32_t)(target - (idx >> 1)) << 16;
  }
  for (int i = tid; i < S_; i += 512) {
    const uint32_t mask = ((i >> 6) & 1) ? LUT_MASK_ODD : LUT_MASK_EVEN;
    const uint32_t o = ((mask >> ((i >> 3) & 7)) & 1) ? 0xBF80BF80u : 0x3F803F80u;
    *reinterpret_cast<uint4*>(sm0 + KS + (i >> 8) * KVCH + 16384 + (i & 255) * 16) = make_uint4(o, o, o, o);
  }
  fence_async_smem();
  __syncthreads();
  if (tid == 0) TS(KID, 5);
  pdl_wait();
  if (tid == 0) TS(KID, 4);
  const int tb = blockIdx.x >> 2, hg = blockIdx.x & 3;
  if (tid == 0) {
    mbar_expect(bars, 16384 + 16384 + 2048);
    bulk_g2s(qst, g_QT + (tb * 8 + hg * 2) * 8192, 16384, bars);
    bulk_g2s(KS, g_KV, 16384, bars);
    bulk_g2s(kred, g_kmax, 2048, bars);
  } else if (tid == 128) {
    mbar_expect(bars + 8, 16384);
    bulk_g2s(KS + KVCH, g_KV + 16384, 16384, bars + 8);
  } else if (tid == 256) {
#pragma unroll 1
    for (int c = 2; c < 8; c++) {
      mbar_expect(bars + c * 8, 16384);
      bulk_g2s(KS + c * KVCH, g_KV + c * 16384, 16384, bars + c * 8);
    }
  }
  __syncwarp();
  const int g = lane >> 2, t = lane & 3;
  mbar_wait(bars, 0);
  if (tid == 0) TS(KID, 6);
  const uint32_t lutlane = LUT | (lane * 4);
  constexpr uint64_t KSTEP = (64 * 32) >> 4, VSTEP = (16 * 16) >> 4;
  constexpr uint64_t KJUMP = (KVCH - 3 * 2048) >> 4, VJUMP = (KVCH - 4096) >> 4;
#pragma unroll 1
  for (int tile = 0; tile < 2; tile++) {
    const int hl = wg * 2 + tile;
    const int arow = warp * 16 + (lane & 15);
    const uint32_t qaddr = qst + (hl >> 2) * 8192 + arow * 128 + ((((hl & 3) * 2 + (lane >> 4)) ^ (arow & 7)) << 4);
    uint32_t q[4];
    ldsm4(q, qaddr);
    float o[12];
#pragma unroll
    for (int i = 0; i < 12; i++) o[i] = 0.f;
    uint64_t kd = mkdesc(KS, 128, 256, 0);
    uint64_t vd = mkdesc(KS + 8192, 128, 4096, 0);
    {
      float s[32];
      uint32_t p[16];
      if (tid == 0 && tile == 0) TS(KID, 1);
      fence_regs<12>(o);
      wg_fence();
      wgmma_rs_n64(s, q[0], q[1], q[2], q[3], kd, 0); kd += KSTEP;
      wg_commit();
#pragma unroll 1
      for (int c = 0; c < 8; c++) {
        if (c < 7) mbar_wait(bars + (c + 1) * 8, 0);
#pragma unroll 1
        for (int j = 0; j < 2; j++) {
          wg_wait<0>(); fence_regs<32>(s); fence_regs<12>(o); fence_regs_u<16>(p);
          exp_pack<LUT_MASK_EVEN>(s, p, lutlane);
          wg_fence();
#pragma unroll
          for (int k = 0; k < 4; k++) { wgmma_rs_tb_n24(o, p[4 * k], p[4 * k + 1], p[4 * k + 2], p[4 * k + 3], vd, 1); vd += VSTEP; }
          wgmma_rs_n64(s, q[0], q[1], q[2], q[3], kd, 0); kd += j ? KJUMP : KSTEP;
          wg_commit();
          wg_wait<0>(); fence_regs<32>(s); fence_regs<12>(o); fence_regs_u<16>(p);
          exp_pack<LUT_MASK_ODD>(s, p, lutlane);
          wg_fence();
#pragma unroll
          for (int k = 0; k < 4; k++) { wgmma_rs_tb_n24(o, p[4 * k], p[4 * k + 1], p[4 * k + 2], p[4 * k + 3], vd, 1); vd += VSTEP; }
          wgmma_rs_n64(s, q[0], q[1], q[2], q[3], kd, 0); kd += KSTEP;
          wg_commit();
        }
        vd += VJUMP;
      }
      wg_wait<0>(); fence_regs<12>(o); fence_regs<32>(s);
    }
    uint32_t unsafe;
    {
      const float4* kr = reinterpret_cast<const float4*>(sm0 + kred);
      float4 m = kr[lane];
#pragma unroll
      for (int i = 1; i < 4; i++) {
        const float4 v = kr[lane + 32 * i];
        m.x = fmaxf(m.x, v.x); m.y = fmaxf(m.y, v.y); m.z = fmaxf(m.z, v.z); m.w = fmaxf(m.w, v.w);
      }
#pragma unroll
      for (int of = 4; of < 32; of <<= 1) {
        m.x = fmaxf(m.x, __shfl_xor_sync(~0u, m.x, of)); m.y = fmaxf(m.y, __shfl_xor_sync(~0u, m.y, of));
        m.z = fmaxf(m.z, __shfl_xor_sync(~0u, m.z, of)); m.w = fmaxf(m.w, __shfl_xor_sync(~0u, m.w, of));
      }
      const float ax = __shfl_sync(~0u, m.x, t >> 1), ay = __shfl_sync(~0u, m.y, t >> 1), az = __shfl_sync(~0u, m.z, t >> 1), aw = __shfl_sync(~0u, m.w, t >> 1);
      const float bx = __shfl_sync(~0u, m.x, 2 + (t >> 1)), by = __shfl_sync(~0u, m.y, 2 + (t >> 1)), bz = __shfl_sync(~0u, m.z, 2 + (t >> 1)),
                  bw = __shfl_sync(~0u, m.w, 2 + (t >> 1));
      const float k0 = (t & 1) ? az : ax, k1 = (t & 1) ? aw : ay, k2 = (t & 1) ? bz : bx, k3 = (t & 1) ? bw : by;
      float b0 = fabsf(bf_lo(q[0])) * k0 + fabsf(bf_hi(q[0])) * k1 + fabsf(bf_lo(q[2])) * k2 + fabsf(bf_hi(q[2])) * k3;
      float b1 = fabsf(bf_lo(q[1])) * k0 + fabsf(bf_hi(q[1])) * k1 + fabsf(bf_lo(q[3])) * k2 + fabsf(bf_hi(q[3])) * k3;
      b0 += __shfl_xor_sync(~0u, b0, 1); b0 += __shfl_xor_sync(~0u, b0, 2);
      b1 += __shfl_xor_sync(~0u, b1, 1); b1 += __shfl_xor_sync(~0u, b1, 2);
      unsafe = __any_sync(~0u, !(b0 <= SAFE_SCORE_BOUND && b1 <= SAFE_SCORE_BOUND)) ? 1u : 0u;
    }
    if (unsafe) {
#pragma unroll
      for (int i = 0; i < 12; i++) o[i] = 0.f;
      float m0 = -INFINITY, m1 = -INFINITY;
#pragma unroll 1
      for (int kb = 0; kb < S_ / 16; kb++) {
        uint32_t kf[4];
        float sa[4] = {0.f, 0.f, 0.f, 0.f}, sc[4] = {0.f, 0.f, 0.f, 0.f};
        ldsm4(kf, KS + (kb >> 4) * KVCH + (kb & 15) * 512 + lane * 16);
        mma16816(sa, q, kf[0], kf[1]);
        mma16816(sc, q, kf[2], kf[3]);
        m0 = fmaxf(fmaxf(m0, fmaxf(sa[0], sa[1])), fmaxf(sc[0], sc[1]));
        m1 = fmaxf(fmaxf(m1, fmaxf(sa[2], sa[3])), fmaxf(sc[2], sc[3]));
      }
      m0 = fmaxf(m0, __shfl_xor_sync(~0u, m0, 1)); m0 = fmaxf(m0, __shfl_xor_sync(~0u, m0, 2));
      m1 = fmaxf(m1, __shfl_xor_sync(~0u, m1, 1)); m1 = fmaxf(m1, __shfl_xor_sync(~0u, m1, 2));
#pragma unroll 1
      for (int kb = 0; kb < S_ / 16; kb++) {
        uint32_t kf[4], vf[4], ef[4], a[4];
        float sa[4] = {0.f, 0.f, 0.f, 0.f}, sc[4] = {0.f, 0.f, 0.f, 0.f};
        const uint32_t chb = KS + (kb >> 4) * KVCH;
        ldsm4(kf, chb + (kb & 15) * 512 + lane * 16);
        const uint32_t krow = chb + 8192 + ((kb & 15) * 16 + (lane & 15)) * 16;
        ldsm4t(vf, krow + (lane >> 4) * 4096);
        ldsm4t(ef, krow + 8192);
        mma16816(sa, q, kf[0], kf[1]);
        mma16816(sc, q, kf[2], kf[3]);
        const uint32_t mask = ((kb >> 2) & 1) ? LUT_MASK_ODD : LUT_MASK_EVEN;
        const uint32_t sg0 = ((mask >> ((2 * kb) & 7)) & 1) ? 0x80008000u : 0u, sg1 = ((mask >> ((2 * kb + 1) & 7)) & 1) ? 0x80008000u : 0u;
        a[0] = pack_bf16(ex2f(sa[0] - m0), ex2f(sa[1] - m0)) ^ sg0;
        a[1] = pack_bf16(ex2f(sa[2] - m1), ex2f(sa[3] - m1)) ^ sg0;
        a[2] = pack_bf16(ex2f(sc[0] - m0), ex2f(sc[1] - m0)) ^ sg1;
        a[3] = pack_bf16(ex2f(sc[2] - m1), ex2f(sc[3] - m1)) ^ sg1;
        mma16816(o, a, vf[0], vf[1]);
        mma16816(o + 4, a, vf[2], vf[3]);
        mma16816(o + 8, a, ef[0], ef[1]);
      }
    }
    const float r0 = 1.f / o[8], r1 = 1.f / o[10];
    stsm4(qst + (hl >> 2) * 8192 + (warp * 16 + ((lane >> 3) & 1) * 8 + (lane & 7)) * 128 +
              ((((hl & 3) * 2 + (lane >> 4)) ^ (lane & 7)) << 4),
          pack_bf16(o[0] * r0, o[1] * r0), pack_bf16(o[2] * r1, o[3] * r1), pack_bf16(o[4] * r0, o[5] * r0), pack_bf16(o[6] * r1, o[7] * r1));
    if (tid == 0 && tile == 0) TS(KID, 2);
  }
  fence_async_smem();
  __syncthreads();
  if (tid == 0) {
    bulk_s2g(g_OT + (tb * 8 + hg * 2) * 8192, qst, 16384);
    bulk_commit_wait_all();
    TS(KID, 3);
  }
}

__device__ __forceinline__ void residual_block(const float* a, uint32_t tile, int warp, int lane, float2* stat_out  ) {
  const int rl = warp * 16 + ((lane >> 3) & 1) * 8 + (lane & 7);
  const uint32_t rowa = tile + rl * 128;
  float s0 = 0.f, q0 = 0.f, s1 = 0.f, q1 = 0.f;
#pragma unroll
  for (int j = 0; j < 8; j += 2) {
    const uint32_t ad = rowa + (((j + (lane >> 4)) ^ (rl & 7)) << 4);
    uint32_t r[4];
    ldsm4(r, ad);
    const float* c = a + 4 * j;
    const uint32_t u0 = pack_bf16(bf_lo(r[0]) + c[0], bf_hi(r[0]) + c[1]);
    const uint32_t u1 = pack_bf16(bf_lo(r[1]) + c[2], bf_hi(r[1]) + c[3]);
    const uint32_t u2 = pack_bf16(bf_lo(r[2]) + c[4], bf_hi(r[2]) + c[5]);
    const uint32_t u3 = pack_bf16(bf_lo(r[3]) + c[6], bf_hi(r[3]) + c[7]);
    s0 += (bf_lo(u0) + bf_hi(u0)) + (bf_lo(u2) + bf_hi(u2));
    q0 += bf_lo(u0) * bf_lo(u0) + bf_hi(u0) * bf_hi(u0) + bf_lo(u2) * bf_lo(u2) + bf_hi(u2) * bf_hi(u2);
    s1 += (bf_lo(u1) + bf_hi(u1)) + (bf_lo(u3) + bf_hi(u3));
    q1 += bf_lo(u1) * bf_lo(u1) + bf_hi(u1) * bf_hi(u1) + bf_lo(u3) * bf_lo(u3) + bf_hi(u3) * bf_hi(u3);
    stsm4(ad, u0, u1, u2, u3);
  }
#pragma unroll
  for (int o = 1; o < 4; o <<= 1) {
    s0 += __shfl_xor_sync(~0u, s0, o); q0 += __shfl_xor_sync(~0u, q0, o);
    s1 += __shfl_xor_sync(~0u, s1, o); q1 += __shfl_xor_sync(~0u, q1, o);
  }
  if ((lane & 3) == 0) {
    stat_out[0] = make_float2(s0, q0);
    stat_out[8 * 8] = make_float2(s1, q1);
  }
}

constexpr int OPJ_CH = 8192 + 16384;
constexpr int OPJ_SMEM = 8 * OPJ_CH + 16384 + 1024 + 256;
__global__ void __launch_bounds__(192, 1) oproj_kernel(const __grid_constant__ CUtensorMap mW, const uint8_t* __restrict__ resT, int KID) {
  extern __shared__ uint8_t smraw[];
  const uint32_t sb = (smem_u32(smraw) + 1023) & ~1023u;
  const uint32_t res = sb + 8 * OPJ_CH, bars = res + 16384;
  const int tid = threadIdx.x, lane = tid & 31, warp = tid >> 5;
  const int tb = blockIdx.x >> 2, ct = blockIdx.x & 3;
  if (tid == 0) TS(KID, 0);
  pdl_trigger();
  if (tid == 0) {
    tmap_prefetch(&mW);
    for (int i = 0; i < 9; i++) mbar_init(bars + i * 8, 1);
    mbar_fence_init();
  }
  __syncthreads();
  if (tid == 128) {
#pragma unroll 1
    for (int kc = 0; kc < 8; kc++) {
      mbar_expect(bars + kc * 8, OPJ_CH);
      tma3d(sb + kc * OPJ_CH + 8192, &mW, 0, kc * 64, ct * 2, bars + kc * 8);
    }
  } else if (tid == 160) {
    TS(KID, 6);
    pdl_wait();
    TS(KID, 5);
#pragma unroll 1
    for (int kc = 0; kc < 8; kc++) bulk_g2s(sb + kc * OPJ_CH, g_OT + (tb * 8 + kc) * 8192, 8192, bars + kc * 8);
    mbar_expect(bars + 64, 16384);
    bulk_g2s(res, resT + (tb * 8 + ct * 2) * 8192, 16384, bars + 64);
  }
  if (warp >= 4) return;
  float acc[64];
#pragma unroll
  for (int i = 0; i < 64; i++) acc[i] = 0.f;
  fence_regs<64>(acc);
#pragma unroll 1
  for (int kc = 0; kc < 8; kc++) {
    const uint32_t st = sb + kc * OPJ_CH;
    mbar_wait(bars + kc * 8, 0);
    if (tid == 0 && kc == 0) TS(KID, 1);
    wg_fence();
#pragma unroll
    for (int ks = 0; ks < 4; ks++)
      wgmma_ss_tb_n128(acc, mkdesc(st + ks * 32, 16, 1024, 1), mkdesc(st + 8192 + ks * 2048, 8192, 1024, 1), 1);
    wg_commit();
  }
  wg_wait<0>();
  fence_regs<64>(acc);
  if (tid == 0) TS(KID, 2);
  pdl_wait();
  mbar_wait(bars + 64, 0);
  const int r0 = tb * 64 + warp * 16 + (lane >> 2);
  residual_block(acc, res, warp, lane, g_statB + r0 * 8 + ct * 2);
  residual_block(acc + 32, res + 8192, warp, lane, g_statB + r0 * 8 + ct * 2 + 1);
  fence_async_smem();
  bar_sync(1, 128);
  if (tid == 0) {
    bulk_s2g(g_x1T + (tb * 8 + ct * 2) * 8192, res, 16384);
    TS(KID, 4);
    bulk_commit_wait_all();
    TS(KID, 3);
  }
}

constexpr int F1_STAGES = 5, F1_A = 16384, F1_B = 28672, F1_STAGE = F1_A + F1_B;
constexpr int F1_AUX = F1_STAGES * F1_STAGE;
constexpr int F1_SMEM = F1_AUX + 128 + 480 * 4 + 1024;
__global__ void __launch_bounds__(320, 1) ffn1_kernel(int early, int KID) {
  extern __shared__ uint8_t smraw[];
  const uint32_t sb = (smem_u32(smraw) + 1023) & ~1023u;
  const uint32_t bars = sb + F1_AUX;
  float* s_mean = reinterpret_cast<float*>(smraw + (sb - smem_u32(smraw)) + F1_AUX + 128);
  float* s_rstd = s_mean + 128;
  float* s_cs = s_rstd + 128;
  const int tid = threadIdx.x, lane = tid & 31, warp = tid >> 5;
  const int mb = blockIdx.x >> 3, fs = blockIdx.x & 7;
  if (tid == 0) TS(KID, 0);
  pdl_trigger();
  if (tid == 0) {
    for (int i = 0; i < F1_STAGES; i++) { mbar_init(bars + i * 8, 1); mbar_init(bars + (F1_STAGES + i) * 8, 8); }
    mbar_fence_init();
  }
  __syncthreads();
  const uint8_t* gA = g_x1T + (size_t)mb * 2 * 65536;
  const uint8_t* gB = g_W1p + (size_t)fs * 8 * F1_B;
  constexpr int F1_PRE = 3;
  if (warp == 8) {
    if (lane == 0) {
      const bool pre = early || pack_ready();
      if (!pre) pdl_wait();
#pragma unroll 1
      for (int kc = 0; kc < F1_STAGES; kc++) {
        mbar_expect(bars + kc * 8, F1_STAGE);
        if (kc < F1_PRE) bulk_g2s(sb + kc * F1_STAGE + F1_A, gB + kc * F1_B, F1_B, bars + kc * 8);
      }
      TS(KID, 6);
      pdl_wait();
      TS(KID, 5);
#pragma unroll 1
      for (int kc = 0; kc < 8; kc++) {
        const int s = kc % F1_STAGES;
        const uint32_t fb = bars + s * 8, st = sb + s * F1_STAGE;
        if (kc >= F1_STAGES) {
          mbar_wait(bars + (F1_STAGES + s) * 8, 0);
          mbar_expect(fb, F1_STAGE);
        }
        bulk_g2s(st, gA + kc * 8192, 8192, fb);
        bulk_g2s(st + 8192, gA + 65536 + kc * 8192, 8192, fb);
        if (kc >= F1_PRE) bulk_g2s(st + F1_A, gB + kc * F1_B, F1_B, fb);
      }
    }
    return;
  }
  if (warp == 9) {
    pdl_wait();
#pragma unroll
    for (int i = 0; i < 4; i++) {
      float mean, rstd;
      row_stats(g_statB, mb * 128 + i * 32 + lane, mean, rstd);
      s_mean[i * 32 + lane] = mean; s_rstd[i * 32 + lane] = rstd;
    }
#pragma unroll
    for (int i = 0; i < 7; i++) s_cs[i * 32 + lane] = __ldcg(g_cs1 + fs * 224 + i * 32 + lane);
    asm volatile("bar.arrive 1, 288;" ::: "memory");
    return;
  }
  const int wg = warp >> 2, w4 = warp & 3;
  float acc[112];
#pragma unroll
  for (int i = 0; i < 112; i++) acc[i] = 0.f;
  fence_regs<112>(acc);
#pragma unroll 1
  for (int kc = 0; kc < 8; kc++) {
    const int s = kc % F1_STAGES;
    const uint32_t st = sb + s * F1_STAGE;
    mbar_wait(bars + s * 8, kc / F1_STAGES);
    if (tid == 0 && kc == 0) TS(KID, 1);
    wg_fence();
#pragma unroll
    for (int ks = 0; ks < 4; ks++)
      wgmma_ss_tb_n224(acc, mkdesc(st + wg * 8192 + ks * 32, 16, 1024, 1), mkdesc(st + F1_A + ks * 1024, 4096, 512, 2), 1);
    wg_commit();
    if (kc >= 1 && kc - 1 < 8 - F1_STAGES) {
      wg_wait<1>();
      if (lane == 0) mbar_arrive(bars + (F1_STAGES + kc - 1) * 8);
    }
  }
  wg_wait<0>();
  fence_regs<112>(acc);
  if (tid == 0) TS(KID, 2);
  pdl_wait();
  bar_sync(1, 288);
  const int g = lane >> 2, t = lane & 3;
  const int rl0 = wg * 64 + w4 * 16 + g;
  const float mean0 = s_mean[rl0], rstd0 = s_rstd[rl0], mean1 = s_mean[rl0 + 8], rstd1 = s_rstd[rl0 + 8];
  const uint32_t stg = sb + wg * 28672;
  const int rl = w4 * 16 + ((lane >> 3) & 1) * 8 + (lane & 7);
  constexpr float NL2E = -1.4426950408889634f;
#pragma unroll
  for (int j = 0; j < 28; j += 2) {
    const float2 ca = *reinterpret_cast<const float2*>(s_cs + 8 * j + 2 * t);
    const float2 cb = *reinterpret_cast<const float2*>(s_cs + 8 * j + 8 + 2 * t);
    const float* a = acc + 4 * j;
    float z[8];
    z[0] = (a[0] - mean0 * ca.x) * rstd0; z[1] = (a[1] - mean0 * ca.y) * rstd0;
    z[2] = (a[2] - mean1 * ca.x) * rstd1; z[3] = (a[3] - mean1 * ca.y) * rstd1;
    z[4] = (a[4] - mean0 * cb.x) * rstd0; z[5] = (a[5] - mean0 * cb.y) * rstd0;
    z[6] = (a[6] - mean1 * cb.x) * rstd1; z[7] = (a[7] - mean1 * cb.y) * rstd1;
#pragma unroll
    for (int i = 0; i < 8; i++) z[i] = __fdividef(z[i], 1.f + ex2f(z[i] * NL2E));
    const int blk = j >> 2, ch = (j & 3) + (lane >> 4);
    stsm4(stg + blk * 4096 + rl * 64 + ((ch ^ ((rl >> 1) & 3)) << 4), pack_bf16(z[0], z[1]), pack_bf16(z[2], z[3]), pack_bf16(z[4], z[5]),
          pack_bf16(z[6], z[7]));
    if (j == 10 || j == 18 || j == 26) {
      fence_async_smem();
      bar_sync(2 + wg, 128);
      if ((tid & 127) == 0) {
        const int b0 = j == 10 ? 0 : (j == 18 ? 3 : 5), nb = j == 10 ? 3 : 2;
        bulk_s2g(g_hT + ((size_t)(mb * 2 + wg) * 56 + fs * 7 + b0) * 4096, stg + b0 * 4096, nb * 4096);
        asm volatile("cp.async.bulk.commit_group;" ::: "memory");
      }
    }
  }
  if ((tid & 127) == 0) {
    if (tid == 0) TS(KID, 4);
    asm volatile("cp.async.bulk.wait_group 0;" ::: "memory");
    if (tid == 0) TS(KID, 3);
  }
}

constexpr int F2_STAGES = 5, F2_STAGE = 32768;
constexpr int F2_SMEM = F2_STAGES * F2_STAGE + 16384 + 32768 + 1024 + 256;
template <bool LAST>
__global__ void __cluster_dims__(2, 1, 1) __launch_bounds__(288, 1)
ffn2_kernel(const __grid_constant__ CUtensorMap mW, const __grid_constant__ CUtensorMap mOut, int KID) {
  extern __shared__ uint8_t smraw[];
  const uint32_t sb = (smem_u32(smraw) + 1023) & ~1023u;
  const uint32_t res = sb + F2_STAGES * F2_STAGE, recv = res + 16384, bars = recv + 32768;
  const int tid = threadIdx.x, lane = tid & 31, warp = tid >> 5;
  const int mb = blockIdx.x >> 3, nt = (blockIdx.x & 7) >> 1, kh = blockIdx.x & 1;
  if (tid == 0) TS(KID, 0);
  pdl_trigger();
  if (tid == 0) {
    tmap_prefetch(&mW);
    if (LAST) tmap_prefetch(&mOut);
    for (int i = 0; i < F2_STAGES; i++) { mbar_init(bars + i * 8, 1); mbar_init(bars + (F2_STAGES + i) * 8, 8); }
    mbar_init(bars + 2 * F2_STAGES * 8, 1);
    mbar_fence_init();
  }
  __syncthreads();
  const uint8_t* gA = g_hT + ((size_t)mb * 2 * 56 + kh * 28) * 4096;
  if (warp == 8) {
    if (lane == 0) {
#pragma unroll 1
      for (int kc = 0; kc < F2_STAGES; kc++) {
        mbar_expect(bars + kc * 8, F2_STAGE);
        tma3d(sb + kc * F2_STAGE + 16384, &mW, 0, kh * 896 + kc * 64, nt * 2, bars + kc * 8);
      }
      TS(KID, 6);
      pdl_wait();
      if (LAST && blockIdx.x == 0) g_pack_done = 0;
      int s = 0, ph = 0;
#pragma unroll 1
      for (int kc = 0; kc < 14; kc++) {
        const uint32_t fb = bars + s * 8, st = sb + s * F2_STAGE;
        if (kc >= F2_STAGES) {
          mbar_wait(bars + (F2_STAGES + s) * 8, ph);
          mbar_expect(fb, F2_STAGE);
        }
        bulk_g2s(st, gA + kc * 8192, 8192, fb);
        bulk_g2s(st + 8192, gA + 56 * 4096 + kc * 8192, 8192, fb);
        if (kc >= F2_STAGES) tma3d(st + 16384, &mW, 0, kh * 896 + kc * 64, nt * 2, fb);
        if (kc == F2_STAGES - 1) {
          const uint32_t rb = bars + 2 * F2_STAGES * 8;
          mbar_expect(rb, 16384);
          bulk_g2s(res, g_x1T + ((mb * 2) * 8 + nt * 2 + kh) * 8192, 8192, rb);
          bulk_g2s(res + 8192, g_x1T + ((mb * 2 + 1) * 8 + nt * 2 + kh) * 8192, 8192, rb);
        }
        if (++s == F2_STAGES) { s = 0; if (kc >= F2_STAGES) ph ^= 1; }
      }
    }
    return;
  }
  const int wg = warp >> 2, w4 = warp & 3;
  float acc[64];
#pragma unroll
  for (int i = 0; i < 64; i++) acc[i] = 0.f;
  fence_regs<64>(acc);
  {
    int s = 0, ph = 0, ps = 0;
#pragma unroll 1
    for (int kc = 0; kc < 14; kc++) {
      const uint32_t st = sb + s * F2_STAGE;
      mbar_wait(bars + s * 8, ph);
      if (tid == 0 && kc == 0) TS(KID, 1);
      wg_fence();
#pragma unroll
      for (int ks = 0; ks < 4; ks++)
        wgmma_ss_tb_n128(acc, mkdesc(st + wg * 8192 + (ks >> 1) * 4096 + (ks & 1) * 32, 16, 512, 2), mkdesc(st + 16384 + ks * 2048, 8192, 1024, 1), 1);
      wg_commit();
      if (kc >= 1) {
        wg_wait<1>();
        if (lane == 0) mbar_arrive(bars + (F2_STAGES + ps) * 8);
      }
      ps = s;
      if (++s == F2_STAGES) { s = 0; ph ^= 1; }
    }
  }
  wg_wait<0>();
  fence_regs<64>(acc);
  if (tid == 0) TS(KID, 2);
  {
    uint32_t dst;
    asm volatile("mapa.shared::cluster.u32 %0, %1, %2;" : "=r"(dst) : "r"(recv + wg * 16384 + (tid & 127) * 16), "r"(kh ^ 1));
#pragma unroll
    for (int i = 0; i < 8; i++) {
      const float x0 = kh ? acc[4 * i] : acc[32 + 4 * i], x1 = kh ? acc[4 * i + 1] : acc[33 + 4 * i];
      const float x2 = kh ? acc[4 * i + 2] : acc[34 + 4 * i], x3 = kh ? acc[4 * i + 3] : acc[35 + 4 * i];
      asm volatile("st.shared::cluster.v4.f32 [%0], {%1,%2,%3,%4};" ::"r"(dst + i * 2048), "f"(x0), "f"(x1), "f"(x2), "f"(x3) : "memory");
    }
  }
  asm volatile("barrier.cluster.arrive.release.aligned;" ::: "memory");
  asm volatile("barrier.cluster.wait.acquire.aligned;" ::: "memory");
  if (tid == 0) TS(KID, 5);
  float fin[32];
#pragma unroll
  for (int i = 0; i < 8; i++) {
    float4 v;
    asm volatile("ld.shared.v4.f32 {%0,%1,%2,%3}, [%4];" : "=f"(v.x), "=f"(v.y), "=f"(v.z), "=f"(v.w) : "r"(recv + wg * 16384 + (tid & 127) * 16 + i * 2048));
    fin[4 * i] = v.x + (kh ? acc[32 + 4 * i] : acc[4 * i]);
    fin[4 * i + 1] = v.y + (kh ? acc[33 + 4 * i] : acc[4 * i + 1]);
    fin[4 * i + 2] = v.z + (kh ? acc[34 + 4 * i] : acc[4 * i + 2]);
    fin[4 * i + 3] = v.w + (kh ? acc[35 + 4 * i] : acc[4 * i + 3]);
  }
  pdl_wait();
  mbar_wait(bars + 2 * F2_STAGES * 8, 0);
  const int r0 = mb * 128 + wg * 64 + w4 * 16 + (lane >> 2);
  residual_block(fin, res + wg * 8192, w4, lane, g_statA + r0 * 8 + nt * 2 + kh);
  fence_async_smem();
  bar_sync(2 + wg, 128);
  if ((tid & 127) == 0) {
    if (LAST) tma2d_store(&mOut, nt * 128 + kh * 64, mb * 128 + wg * 64, res + wg * 8192);
    else bulk_s2g(g_x2T + ((mb * 2 + wg) * 8 + nt * 2 + kh) * 8192, res + wg * 8192, 8192);
    if (tid == 0) TS(KID, 4);
    bulk_commit_wait_all();
    if (tid == 0) TS(KID, 3);
    if (LAST && tid == 0 && blockIdx.x == 0) GT(1);
  }
}

typedef CUresult (*EncodeFn)(CUtensorMap*, CUtensorMapDataType, cuuint32_t, void*, const cuuint64_t*, const cuuint64_t*, const cuuint32_t*,
                             const cuuint32_t*, CUtensorMapInterleave, CUtensorMapSwizzle, CUtensorMapL2promotion, CUtensorMapFloatOOBfill);

CUtensorMap make_map(EncodeFn fn, const void* base, int rank, const cuuint64_t* dims, const cuuint64_t* strides, const cuuint32_t* box,
                     CUtensorMapSwizzle swz) {
  CUtensorMap m;
  cuuint32_t es[3] = {1, 1, 1};
  fn(&m, CU_TENSOR_MAP_DATA_TYPE_BFLOAT16, rank, const_cast<void*>(base), dims, strides, box, es, CU_TENSOR_MAP_INTERLEAVE_NONE, swz,
     CU_TENSOR_MAP_L2_PROMOTION_NONE, CU_TENSOR_MAP_FLOAT_OOB_FILL_NONE);
  return m;
}
CUtensorMap map2d(EncodeFn fn, const void* base, int rows, int cols, int box_rows) {
  cuuint64_t dims[2] = {(cuuint64_t)cols, (cuuint64_t)rows}, strides[1] = {(cuuint64_t)cols * 2};
  cuuint32_t box[2] = {64, (cuuint32_t)box_rows};
  return make_map(fn, base, 2, dims, strides, box, CU_TENSOR_MAP_SWIZZLE_128B);
}
CUtensorMap map3d(EncodeFn fn, const void* base, int rows, int cols, int inner, int box_rows, int box_blocks) {
  cuuint64_t dims[3] = {(cuuint64_t)inner, (cuuint64_t)rows, (cuuint64_t)(cols / inner)};
  cuuint64_t strides[2] = {(cuuint64_t)cols * 2, (cuuint64_t)inner * 2};
  cuuint32_t box[3] = {(cuuint32_t)inner, (cuuint32_t)box_rows, (cuuint32_t)box_blocks};
  return make_map(fn, base, 3, dims, strides, box, inner == 64 ? CU_TENSOR_MAP_SWIZZLE_128B : CU_TENSOR_MAP_SWIZZLE_64B);
}

template <typename... KArgs, typename... Args>
void launch(void (*kern)(KArgs...), int grid, int block, int smem, bool pdl, Args... args) {
  cudaLaunchConfig_t cfg = {};
  cfg.gridDim = dim3(grid);
  cfg.blockDim = dim3(block);
  cfg.dynamicSmemBytes = smem;
  cfg.stream = cudaStreamPerThread;
  cudaLaunchAttribute at[1];
  at[0].id = cudaLaunchAttributeProgrammaticStreamSerialization;
  at[0].val.programmaticStreamSerializationAllowed = 1;
  cfg.attrs = at;
  cfg.numAttrs = pdl ? 1 : 0;
  cudaLaunchKernelEx(&cfg, kern, args...);
}

}

extern "C" void kernel_launch(void* const* d_in, const int* in_sizes, int n_in, void* d_out, int out_size) {
  const bf16* x = (const bf16*)d_in[0];
  const bf16* wq = (const bf16*)d_in[1];
  const bf16* wk = (const bf16*)d_in[2];
  const bf16* wv = (const bf16*)d_in[3];
  const bf16* wo = (const bf16*)d_in[4];
  const bf16* w1 = (const bf16*)d_in[6];
  const bf16* w2 = (const bf16*)d_in[7];

  void* fp = nullptr;
  cudaDriverEntryPointQueryResult qr;
  cudaGetDriverEntryPoint("cuTensorMapEncodeTiled", &fp, cudaEnableDefault, &qr);
  EncodeFn fn = (EncodeFn)fp;
  const CUtensorMap mOut = map2d(fn, d_out, S_, D_, 64), mX = map2d(fn, x, S_, D_, 64);
  const CUtensorMap mWq = map3d(fn, wq, D_, D_, 64, 64, 2), mWo = map3d(fn, wo, D_, D_, 64, 64, 2);
  const CUtensorMap mW1 = map3d(fn, w1, D_, F_, 32, 64, 7), mW2 = map3d(fn, w2, F_, D_, 64, 64, 2);

  cudaFuncSetAttribute(qkv_kernel<true>, cudaFuncAttributeMaxDynamicSharedMemorySize, QKV_SMEM);
  cudaFuncSetAttribute(qkv_kernel<false>, cudaFuncAttributeMaxDynamicSharedMemorySize, QKV_SMEM);
  cudaFuncSetAttribute(attn_kernel, cudaFuncAttributeMaxDynamicSharedMemorySize, ATT_SMEM);
  cudaFuncSetAttribute(oproj_kernel, cudaFuncAttributeMaxDynamicSharedMemorySize, OPJ_SMEM);
  cudaFuncSetAttribute(ffn1_kernel, cudaFuncAttributeMaxDynamicSharedMemorySize, F1_SMEM);
  cudaFuncSetAttribute(ffn2_kernel<false>, cudaFuncAttributeMaxDynamicSharedMemorySize, F2_SMEM);
  cudaFuncSetAttribute(ffn2_kernel<true>, cudaFuncAttributeMaxDynamicSharedMemorySize, F2_SMEM);
  void *pX0T, *pX2T;
  cudaGetSymbolAddress(&pX0T, g_x0T);
  cudaGetSymbolAddress(&pX2T, g_x2T);

  for (int layer = 0; layer < 2; layer++) {
    if (layer == 0) launch(qkv_kernel<true>, 128, 256, QKV_SMEM, false, mX, mWq, wk, wv);
    else launch(qkv_kernel<false>, 128, 256, QKV_SMEM, true, mX, mWq, wk, wv);
    launch(attn_kernel, layer == 0 ? 128 + (int)NPACK : 128, 512, ATT_SMEM, true, mW1, wo, w2, 2 + layer * 5);
    launch(oproj_kernel, 128, 192, OPJ_SMEM, true, mWo, (const uint8_t*)(layer == 0 ? pX0T : pX2T), 3 + layer * 5);
    launch(ffn1_kernel, 128, 320, F1_SMEM, true, layer, 4 + layer * 5);
    if (layer == 0) launch(ffn2_kernel<false>, 128, 288, F2_SMEM, true, mW2, mOut, 5 + layer * 5);
    else launch(ffn2_kernel<true>, 128, 288, F2_SMEM, true, mW2, mOut, 5 + layer * 5);
  }
}
```

```cpp
#include <cuda_runtime.h>
#include <cuda_bf16.h>
#include <cuda.h>
#include <stdint.h>

namespace {

typedef __nv_bfloat16 bf16;
constexpr int S_ = 2048, D_ = 512, F_ = 1792;
constexpr float LN_EPS = 1e-5f;
constexpr float QSCALE = 0.25f * 1.4426950408889634f;

constexpr uint32_t LUT_MASK_EVEN = 0x55, LUT_MASK_ODD = 0x5D;
constexpr float SAFE_SCORE_BOUND = 80.0f;

__device__ __align__(1024) uint8_t g_QT[S_ * D_ * 2];
__device__ __align__(1024) uint8_t g_KV[S_ * 64];
__device__ __align__(1024) float g_kmax[32 * 16];
__device__ __align__(1024) uint8_t g_x0T[S_ * D_ * 2];
__device__ __align__(1024) uint8_t g_OT[S_ * D_ * 2];
__device__ __align__(1024) uint8_t g_x1T[S_ * D_ * 2];
__device__ __align__(1024) uint8_t g_x2T[S_ * D_ * 2];
__device__ __align__(1024) uint8_t g_hT[S_ * F_ * 2];
__device__ __align__(1024) float2 g_statA[S_ * 8];
__device__ __align__(1024) float2 g_statB[S_ * 8];
__device__ __align__(1024) float g_csQKV[4 * 136];
__device__ __align__(1024) float g_cs1[F_];
__device__ __align__(1024) uint8_t g_W1p[8 * 8 * 28672];
__device__ unsigned g_pack_done;
constexpr unsigned NPACK = 4;

#define TS(kid, slot)
#define GT(i)
__device__ __forceinline__ uint32_t smem_u32(const void* p) { return (uint32_t)__cvta_generic_to_shared(p); }
__device__ __forceinline__ void mbar_init(uint32_t b, uint32_t c) { asm volatile("mbarrier.init.shared::cta.b64 [%0], %1;" ::"r"(b), "r"(c)); }
__device__ __forceinline__ void mbar_fence_init() { asm volatile("fence.mbarrier_init.release.cluster;" ::: "memory"); }
__device__ __forceinline__ void mbar_expect(uint32_t b, uint32_t bytes) {
  asm volatile("mbarrier.arrive.expect_tx.shared::cta.b64 _, [%0], %1;" ::"r"(b), "r"(bytes) : "memory");
}
__device__ __forceinline__ void mbar_arrive(uint32_t b) { asm volatile("mbarrier.arrive.shared::cta.b64 _, [%0];" ::"r"(b) : "memory"); }
__device__ __forceinline__ void mbar_wait(uint32_t b, uint32_t ph) {
  asm volatile(
      "{.reg .pred p;\n"
      "LAB_WAIT:\n"
      "mbarrier.try_wait.parity.shared::cta.b64 p, [%0], %1;\n"
      "@p bra LAB_DONE;\n"
      "bra LAB_WAIT;\n"
      "LAB_DONE:\n}" ::"r"(b), "r"(ph) : "memory");
}
__device__ __forceinline__ void bulk_g2s(uint32_t dst, const void* src, uint32_t bytes, uint32_t bar) {
  asm volatile("cp.async.bulk.shared::cluster.global.mbarrier::complete_tx::bytes [%0], [%1], %2, [%3];" ::"r"(dst), "l"(src), "r"(bytes), "r"(bar) : "memory");
}
__device__ __forceinline__ void bulk_s2g(void* dst, uint32_t src, uint32_t bytes) {
  asm volatile("cp.async.bulk.global.shared::cta.bulk_group [%0], [%1], %2;" ::"l"(dst), "r"(src), "r"(bytes) : "memory");
}
__device__ __forceinline__ bool pack_ready() {
  unsigned v;
  asm volatile("ld.acquire.gpu.global.u32 %0, [%1];" : "=r"(v) : "l"(&g_pack_done) : "memory");
  return v == NPACK;
}
__device__ __forceinline__ void tma2d(uint32_t dst, const CUtensorMap* m, int c0, int c1, uint32_t bar) {
  asm volatile("cp.async.bulk.tensor.2d.shared::cluster.global.mbarrier::complete_tx::bytes [%0], [%1, {%3, %4}], [%2];"
               ::"r"(dst), "l"(m), "r"(bar), "r"(c0), "r"(c1) : "memory");
}
__device__ __forceinline__ void tma3d(uint32_t dst, const CUtensorMap* m, int c0, int c1, int c2, uint32_t bar) {
  asm volatile("cp.async.bulk.tensor.3d.shared::cluster.global.mbarrier::complete_tx::bytes [%0], [%1, {%3, %4, %5}], [%2];"
               ::"r"(dst), "l"(m), "r"(bar), "r"(c0), "r"(c1), "r"(c2) : "memory");
}
__device__ __forceinline__ void tmap_prefetch(const CUtensorMap* m) { asm volatile("prefetch.tensormap [%0];" ::"l"(m) : "memory"); }
__device__ __forceinline__ void tma2d_store(const CUtensorMap* m, int c0, int c1, uint32_t src) {
  asm volatile("cp.async.bulk.tensor.2d.global.shared::cta.bulk_group [%0, {%2, %3}], [%1];" ::"l"(m), "r"(src), "r"(c0), "r"(c1) : "memory");
}
__device__ __forceinline__ void bulk_commit_wait_all() {
  asm volatile("cp.async.bulk.commit_group;" ::: "memory");
  asm volatile("cp.async.bulk.wait_group 0;" ::: "memory");
}
__device__ __forceinline__ void fence_async_smem() { asm volatile("fence.proxy.async.shared::cta;" ::: "memory"); }
__device__ __forceinline__ void pdl_trigger() { asm volatile("griddepcontrol.launch_dependents;" ::: "memory"); }
__device__ __forceinline__ void pdl_wait() { asm volatile("griddepcontrol.wait;" ::: "memory"); }
__device__ __forceinline__ void bar_sync(int id, int n) { asm volatile("bar.sync %0, %1;" ::"r"(id), "r"(n) : "memory"); }
__device__ __forceinline__ void wg_fence() { asm volatile("wgmma.fence.sync.aligned;" ::: "memory"); }
__device__ __forceinline__ void wg_commit() { asm volatile("wgmma.commit_group.sync.aligned;" ::: "memory"); }
template <int N> __device__ __forceinline__ void wg_wait() { asm volatile("wgmma.wait_group.sync.aligned %0;" ::"n"(N) : "memory"); }
__device__ __forceinline__ uint64_t mkdesc(uint32_t addr, uint32_t lbo, uint32_t sbo, uint32_t swz) {
  return (uint64_t)((addr & 0x3FFFF) >> 4) | ((uint64_t)(lbo >> 4) << 16) | ((uint64_t)(sbo >> 4) << 32) | ((uint64_t)swz << 62);
}
template <int N> __device__ __forceinline__ void fence_regs(float* d) {
#pragma unroll
  for (int i = 0; i < N; i++) asm volatile("" : "+f"(d[i])::"memory");
}
template <int N> __device__ __forceinline__ void fence_regs_u(uint32_t* d) {
#pragma unroll
  for (int i = 0; i < N; i++) asm volatile("" : "+r"(d[i])::"memory");
}
__device__ __forceinline__ uint32_t pack_bf16(float lo, float hi) {
  uint32_t r;
  asm("cvt.rn.bf16x2.f32 %0, %1, %2;" : "=r"(r) : "f"(hi), "f"(lo));
  return r;
}
__device__ __forceinline__ float bf_lo(uint32_t u) { return __uint_as_float(u << 16); }
__device__ __forceinline__ float bf_hi(uint32_t u) { return __uint_as_float(u & 0xFFFF0000u); }
__device__ __forceinline__ float ex2f(float x) {
  float y;
  asm("ex2.approx.ftz.f32 %0, %1;" : "=f"(y) : "f"(x));
  return y;
}
__device__ __forceinline__ void stsm4(uint32_t a, uint32_t r0, uint32_t r1, uint32_t r2, uint32_t r3) {
  asm volatile("stmatrix.sync.aligned.m8n8.x4.shared.b16 [%0], {%1,%2,%3,%4};" ::"r"(a), "r"(r0), "r"(r1), "r"(r2), "r"(r3) : "memory");
}
__device__ __forceinline__ void ldsm4(uint32_t* r, uint32_t a) {
  asm volatile("ldmatrix.sync.aligned.m8n8.x4.shared.b16 {%0,%1,%2,%3}, [%4];" : "=r"(r[0]), "=r"(r[1]), "=r"(r[2]), "=r"(r[3]) : "r"(a) : "memory");
}
__device__ __forceinline__ void ldsm4t(uint32_t* r, uint32_t a) {
  asm volatile("ldmatrix.sync.aligned.m8n8.x4.trans.shared.b16 {%0,%1,%2,%3}, [%4];" : "=r"(r[0]), "=r"(r[1]), "=r"(r[2]), "=r"(r[3]) : "r"(a) : "memory");
}
__device__ __forceinline__ void mma16816(float* d, const uint32_t* a, uint32_t b0, uint32_t b1) {
  asm volatile("mma.sync.aligned.m16n8k16.row.col.f32.bf16.bf16.f32 {%0,%1,%2,%3}, {%4,%5,%6,%7}, {%8,%9}, {%0,%1,%2,%3};"
               : "+f"(d[0]), "+f"(d[1]), "+f"(d[2]), "+f"(d[3]) : "r"(a[0]), "r"(a[1]), "r"(a[2]), "r"(a[3]), "r"(b0), "r"(b1));
}
__device__ __forceinline__ void row_stats(const float2* __restrict__ st, int row, float& mean, float& rstd) {
  const float4* p = reinterpret_cast<const float4*>(st + row * 8);
  float s = 0.f, q = 0.f;
#pragma unroll
  for (int i = 0; i < 4; i++) {
    float4 v = __ldcg(p + i);
    s += v.x + v.z;
    q += v.y + v.w;
  }
  mean = s * (1.f / D_);
  float var = fmaxf(q * (1.f / D_) - mean * mean, 0.f);
  rstd = rsqrtf(var + LN_EPS);
}

__device__ __forceinline__ void wgmma_rs_n64(float* d, uint32_t a0, uint32_t a1, uint32_t a2, uint32_t a3, uint64_t descB, int scaleD){
  asm volatile("{.reg .pred p; setp.ne.b32 p, %37, 0; wgmma.mma_async.sync.aligned.m64n64k16.f32.bf16.bf16 {%0,%1,%2,%3,%4,%5,%6,%7,%8,%9,%10,%11,%12,%13,%14,%15,%16,%17,%18,%19,%20,%21,%22,%23,%24,%25,%26,%27,%28,%29,%30,%31}, {%32,%33,%34,%35}, %36, p, 1, 1, 0;}"
   : "+f"(d[0]),"+f"(d[1]),"+f"(d[2]),"+f"(d[3]),"+f"(d[4]),"+f"(d[5]),"+f"(d[6]),"+f"(d[7]),"+f"(d[8]),"+f"(d[9]),"+f"(d[10]),"+f"(d[11]),"+f"(d[12]),"+f"(d[13]),"+f"(d[14]),"+f"(d[15]),"+f"(d[16]),"+f"(d[17]),"+f"(d[18]),"+f"(d[19]),"+f"(d[20]),"+f"(d[21]),"+f"(d[22]),"+f"(d[23]),"+f"(d[24]),"+f"(d[25]),"+f"(d[26]),"+f"(d[27]),"+f"(d[28]),"+f"(d[29]),"+f"(d[30]),"+f"(d[31])
   : "r"(a0),"r"(a1),"r"(a2),"r"(a3),"l"(descB),"r"(scaleD));
}

__device__ __forceinline__ void wgmma_rs_tb_n24(float* d, uint32_t a0, uint32_t a1, uint32_t a2, uint32_t a3, uint64_t descB, int scaleD){
  asm volatile("{.reg .pred p; setp.ne.b32 p, %17, 0; wgmma.mma_async.sync.aligned.m64n24k16.f32.bf16.bf16 {%0,%1,%2,%3,%4,%5,%6,%7,%8,%9,%10,%11}, {%12,%13,%14,%15}, %16, p, 1, 1, 1;}"
   : "+f"(d[0]),"+f"(d[1]),"+f"(d[2]),"+f"(d[3]),"+f"(d[4]),"+f"(d[5]),"+f"(d[6]),"+f"(d[7]),"+f"(d[8]),"+f"(d[9]),"+f"(d[10]),"+f"(d[11])
   : "r"(a0),"r"(a1),"r"(a2),"r"(a3),"l"(descB),"r"(scaleD));
}

__device__ __forceinline__ void wgmma_ss_tb_n128(float* d, uint64_t descA, uint64_t descB, int scaleD){
  asm volatile("{.reg .pred p; setp.ne.b32 p, %66, 0; wgmma.mma_async.sync.aligned.m64n128k16.f32.bf16.bf16 {%0,%1,%2,%3,%4,%5,%6,%7,%8,%9,%10,%11,%12,%13,%14,%15,%16,%17,%18,%19,%20,%21,%22,%23,%24,%25,%26,%27,%28,%29,%30,%31,%32,%33,%34,%35,%36,%37,%38,%39,%40,%41,%42,%43,%44,%45,%46,%47,%48,%49,%50,%51,%52,%53,%54,%55,%56,%57,%58,%59,%60,%61,%62,%63}, %64, %65, p, 1, 1, 0, 1;}"
   : "+f"(d[0]),"+f"(d[1]),"+f"(d[2]),"+f"(d[3]),"+f"(d[4]),"+f"(d[5]),"+f"(d[6]),"+f"(d[7]),"+f"(d[8]),"+f"(d[9]),"+f"(d[10]),"+f"(d[11]),"+f"(d[12]),"+f"(d[13]),"+f"(d[14]),"+f"(d[15]),"+f"(d[16]),"+f"(d[17]),"+f"(d[18]),"+f"(d[19]),"+f"(d[20]),"+f"(d[21]),"+f"(d[22]),"+f"(d[23]),"+f"(d[24]),"+f"(d[25]),"+f"(d[26]),"+f"(d[27]),"+f"(d[28]),"+f"(d[29]),"+f"(d[30]),"+f"(d[31]),"+f"(d[32]),"+f"(d[33]),"+f"(d[34]),"+f"(d[35]),"+f"(d[36]),"+f"(d[37]),"+f"(d[38]),"+f"(d[39]),"+f"(d[40]),"+f"(d[41]),"+f"(d[42]),"+f"(d[43]),"+f"(d[44]),"+f"(d[45]),"+f"(d[46]),"+f"(d[47]),"+f"(d[48]),"+f"(d[49]),"+f"(d[50]),"+f"(d[51]),"+f"(d[52]),"+f"(d[53]),"+f"(d[54]),"+f"(d[55]),"+f"(d[56]),"+f"(d[57]),"+f"(d[58]),"+f"(d[59]),"+f"(d[60]),"+f"(d[61]),"+f"(d[62]),"+f"(d[63])
   : "l"(descA),"l"(descB),"r"(scaleD));
}

__device__ __forceinline__ void wgmma_ss_tb_n136(float* d, uint64_t descA, uint64_t descB, int scaleD){
  asm volatile("{.reg .pred p; setp.ne.b32 p, %70, 0; wgmma.mma_async.sync.aligned.m64n136k16.f32.bf16.bf16 {%0,%1,%2,%3,%4,%5,%6,%7,%8,%9,%10,%11,%12,%13,%14,%15,%16,%17,%18,%19,%20,%21,%22,%23,%24,%25,%26,%27,%28,%29,%30,%31,%32,%33,%34,%35,%36,%37,%38,%39,%40,%41,%42,%43,%44,%45,%46,%47,%48,%49,%50,%51,%52,%53,%54,%55,%56,%57,%58,%59,%60,%61,%62,%63,%64,%65,%66,%67}, %68, %69, p, 1, 1, 0, 1;}"
   : "+f"(d[0]),"+f"(d[1]),"+f"(d[2]),"+f"(d[3]),"+f"(d[4]),"+f"(d[5]),"+f"(d[6]),"+f"(d[7]),"+f"(d[8]),"+f"(d[9]),"+f"(d[10]),"+f"(d[11]),"+f"(d[12]),"+f"(d[13]),"+f"(d[14]),"+f"(d[15]),"+f"(d[16]),"+f"(d[17]),"+f"(d[18]),"+f"(d[19]),"+f"(d[20]),"+f"(d[21]),"+f"(d[22]),"+f"(d[23]),"+f"(d[24]),"+f"(d[25]),"+f"(d[26]),"+f"(d[27]),"+f"(d[28]),"+f"(d[29]),"+f"(d[30]),"+f"(d[31]),"+f"(d[32]),"+f"(d[33]),"+f"(d[34]),"+f"(d[35]),"+f"(d[36]),"+f"(d[37]),"+f"(d[38]),"+f"(d[39]),"+f"(d[40]),"+f"(d[41]),"+f"(d[42]),"+f"(d[43]),"+f"(d[44]),"+f"(d[45]),"+f"(d[46]),"+f"(d[47]),"+f"(d[48]),"+f"(d[49]),"+f"(d[50]),"+f"(d[51]),"+f"(d[52]),"+f"(d[53]),"+f"(d[54]),"+f"(d[55]),"+f"(d[56]),"+f"(d[57]),"+f"(d[58]),"+f"(d[59]),"+f"(d[60]),"+f"(d[61]),"+f"(d[62]),"+f"(d[63]),"+f"(d[64]),"+f"(d[65]),"+f"(d[66]),"+f"(d[67])
   : "l"(descA),"l"(descB),"r"(scaleD));
}

__device__ __forceinline__ void wgmma_ss_tb_n224(float* d, uint64_t descA, uint64_t descB, int scaleD){
  asm volatile("{.reg .pred p; setp.ne.b32 p, %114, 0; wgmma.mma_async.sync.aligned.m64n224k16.f32.bf16.bf16 {%0,%1,%2,%3,%4,%5,%6,%7,%8,%9,%10,%11,%12,%13,%14,%15,%16,%17,%18,%19,%20,%21,%22,%23,%24,%25,%26,%27,%28,%29,%30,%31,%32,%33,%34,%35,%36,%37,%38,%39,%40,%41,%42,%43,%44,%45,%46,%47,%48,%49,%50,%51,%52,%53,%54,%55,%56,%57,%58,%59,%60,%61,%62,%63,%64,%65,%66,%67,%68,%69,%70,%71,%72,%73,%74,%75,%76,%77,%78,%79,%80,%81,%82,%83,%84,%85,%86,%87,%88,%89,%90,%91,%92,%93,%94,%95,%96,%97,%98,%99,%100,%101,%102,%103,%104,%105,%106,%107,%108,%109,%110,%111}, %112, %113, p, 1, 1, 0, 1;}"
   : "+f"(d[0]),"+f"(d[1]),"+f"(d[2]),"+f"(d[3]),"+f"(d[4]),"+f"(d[5]),"+f"(d[6]),"+f"(d[7]),"+f"(d[8]),"+f"(d[9]),"+f"(d[10]),"+f"(d[11]),"+f"(d[12]),"+f"(d[13]),"+f"(d[14]),"+f"(d[15]),"+f"(d[16]),"+f"(d[17]),"+f"(d[18]),"+f"(d[19]),"+f"(d[20]),"+f"(d[21]),"+f"(d[22]),"+f"(d[23]),"+f"(d[24]),"+f"(d[25]),"+f"(d[26]),"+f"(d[27]),"+f"(d[28]),"+f"(d[29]),"+f"(d[30]),"+f"(d[31]),"+f"(d[32]),"+f"(d[33]),"+f"(d[34]),"+f"(d[35]),"+f"(d[36]),"+f"(d[37]),"+f"(d[38]),"+f"(d[39]),"+f"(d[40]),"+f"(d[41]),"+f"(d[42]),"+f"(d[43]),"+f"(d[44]),"+f"(d[45]),"+f"(d[46]),"+f"(d[47]),"+f"(d[48]),"+f"(d[49]),"+f"(d[50]),"+f"(d[51]),"+f"(d[52]),"+f"(d[53]),"+f"(d[54]),"+f"(d[55]),"+f"(d[56]),"+f"(d[57]),"+f"(d[58]),"+f"(d[59]),"+f"(d[60]),"+f"(d[61]),"+f"(d[62]),"+f"(d[63]),"+f"(d[64]),"+f"(d[65]),"+f"(d[66]),"+f"(d[67]),"+f"(d[68]),"+f"(d[69]),"+f"(d[70]),"+f"(d[71]),"+f"(d[72]),"+f"(d[73]),"+f"(d[74]),"+f"(d[75]),"+f"(d[76]),"+f"(d[77]),"+f"(d[78]),"+f"(d[79]),"+f"(d[80]),"+f"(d[81]),"+f"(d[82]),"+f"(d[83]),"+f"(d[84]),"+f"(d[85]),"+f"(d[86]),"+f"(d[87]),"+f"(d[88]),"+f"(d[89]),"+f"(d[90]),"+f"(d[91]),"+f"(d[92]),"+f"(d[93]),"+f"(d[94]),"+f"(d[95]),"+f"(d[96]),"+f"(d[97]),"+f"(d[98]),"+f"(d[99]),"+f"(d[100]),"+f"(d[101]),"+f"(d[102]),"+f"(d[103]),"+f"(d[104]),"+f"(d[105]),"+f"(d[106]),"+f"(d[107]),"+f"(d[108]),"+f"(d[109]),"+f"(d[110]),"+f"(d[111])
   : "l"(descA),"l"(descB),"r"(scaleD));
}

constexpr int QKV_CH = 8192 + 16384;
constexpr int QKV_KV = 8 * QKV_CH;
constexpr int QKV_AUX = QKV_KV + 8192;
constexpr int QKV_SMEM = QKV_AUX + 2048 + 1024;

template <bool FIRST>
__global__ void __launch_bounds__(FIRST ? 384 : 256, 1) qkv_kernel(const __grid_constant__ CUtensorMap mX, const __grid_constant__ CUtensorMap mWq,
                                                      const bf16* __restrict__ wk, const bf16* __restrict__ wv) {
  extern __shared__ uint8_t smraw[];
  const uint32_t sb = (smem_u32(smraw) + 1023) & ~1023u;
  uint8_t* sp = smraw + (sb - smem_u32(smraw));
  float* s_mean = reinterpret_cast<float*>(sp + QKV_AUX);
  float* s_rstd = s_mean + 64;
  float* s_cs = s_rstd + 64;
  float* s_km = s_cs + 128;
  const uint32_t bars = sb + QKV_AUX + 1536;
  const int tid = threadIdx.x, lane = tid & 31, warp = tid >> 5;
  const int tb = blockIdx.x >> 2, hg = blockIdx.x & 3;
  const int KID = FIRST ? 1 : 6;
  if (tid == 0) TS(KID, 0);
  if (FIRST && tid == 0 && blockIdx.x == 0) GT(0);
  pdl_trigger();
  if (tid == 0) {
    tmap_prefetch(&mWq);
    if (FIRST) tmap_prefetch(&mX);
    for (int i = 0; i < 8; i++) mbar_init(bars + i * 8, 1);
    mbar_fence_init();
  }
  __syncthreads();
  if (tid == 128) {
#pragma unroll 1
    for (int kc = 0; kc < 8; kc++) {
      mbar_expect(bars + kc * 8, QKV_CH);
      tma3d(sb + kc * QKV_CH + 8192, &mWq, 0, kc * 64, hg * 2, bars + kc * 8);
    }
  } else if (tid == 160) {
    if (!FIRST) { pdl_wait(); TS(KID, 5); }
#pragma unroll 1
    for (int kc = 0; kc < 8; kc++) {
      if (FIRST) tma2d(sb + kc * QKV_CH, &mX, kc * 64, tb * 64, bars + kc * 8);
      else bulk_g2s(sb + kc * QKV_CH, g_x2T + (tb * 8 + kc) * 8192, 8192, bars + kc * 8);
    }
  }
  __syncwarp();
  const int g = lane >> 2, t = lane & 3;
  constexpr int NSYNC = FIRST ? 384 : 256;
  if (FIRST && warp >= 8) {
    const int t1 = tid & 127, cg = t1 >> 3, kr = t1 & 7;
    float cs[8];
#pragma unroll
    for (int i = 0; i < 8; i++) cs[i] = 0.f;
#pragma unroll 1
    for (int kc = 0; kc < 8; kc++) {
      mbar_wait(bars + kc * 8, 0);
      const uint8_t* bp = sp + kc * QKV_CH + 8192 + (cg >> 3) * 8192 + kr * 128 + (((cg & 7) ^ kr) << 4);
#pragma unroll
      for (int kg = 0; kg < 8; kg++) {
        const uint4 v = *reinterpret_cast<const uint4*>(bp + kg * 1024);
        cs[0] += bf_lo(v.x); cs[1] += bf_hi(v.x); cs[2] += bf_lo(v.y); cs[3] += bf_hi(v.y);
        cs[4] += bf_lo(v.z); cs[5] += bf_hi(v.z); cs[6] += bf_lo(v.w); cs[7] += bf_hi(v.w);
      }
    }
#pragma unroll
    for (int i = 0; i < 8; i++) {
#pragma unroll
      for (int o = 1; o < 8; o <<= 1) cs[i] += __shfl_xor_sync(~0u, cs[i], o);
    }
    if (kr == 0) {
#pragma unroll
      for (int i = 0; i < 8; i++) { s_cs[cg * 8 + i] = cs[i]; if (tb == 0) g_csQKV[hg * 136 + cg * 8 + i] = cs[i]; }
    }
    asm volatile("bar.arrive 1, 384;" ::: "memory");
    return;
  }
  if (warp >= 4) {
    const int t1 = tid & 127, w4 = warp & 3;
    const bf16* wkv = (hg < 2 ? wk : wv) + (hg & 1) * 8;
    {
      uint4 v[4];
#pragma unroll
      for (int i = 0; i < 4; i++) v[i] = __ldg(reinterpret_cast<const uint4*>(wkv + (size_t)(i * 128 + t1) * 16));
#pragma unroll
      for (int i = 0; i < 4; i++) *reinterpret_cast<uint4*>(sp + QKV_KV + (i * 128 + t1) * 16) = v[i];
    }
    float mean0, rstd0, mean1, rstd1, ck0, ck1;
    const int rl0 = w4 * 16 + g, r0 = tb * 64 + rl0;
    if (!FIRST) {
      s_cs[t1] = __ldcg(g_csQKV + hg * 136 + t1);
      ck0 = __ldcg(g_csQKV + hg * 136 + 128 + 2 * t);
      ck1 = __ldcg(g_csQKV + hg * 136 + 128 + 2 * t + 1);
      pdl_wait();
      row_stats(g_statA, r0, mean0, rstd0);
      row_stats(g_statA, r0 + 8, mean1, rstd1);
      if (t == 0) { s_mean[rl0] = mean0; s_rstd[rl0] = rstd0; s_mean[rl0 + 8] = mean1; s_rstd[rl0 + 8] = rstd1; }
      asm volatile("bar.arrive 1, 256;" ::: "memory");
    }
    bar_sync(2, 128);
    float kv[4] = {0.f, 0.f, 0.f, 0.f}, kw[4] = {0.f, 0.f, 0.f, 0.f}, ones[4] = {0.f, 0.f, 0.f, 0.f};
    float rs0 = 0.f, rq0 = 0.f, rs1 = 0.f, rq1 = 0.f;
    const int arow = w4 * 16 + (lane & 15);
#pragma unroll 1
    for (int kc = 0; kc < 8; kc++) {
      mbar_wait(bars + kc * 8, 0);
      const uint32_t st = sb + kc * QKV_CH;
      uint32_t a[4][4], b[2][4];
#pragma unroll
      for (int ks = 0; ks < 4; ks++) ldsm4(a[ks], st + arow * 128 + (((ks * 2 + (lane >> 4)) ^ (arow & 7)) << 4));
      ldsm4t(b[0], sb + QKV_KV + (kc * 64 + lane) * 16);
      ldsm4t(b[1], sb + QKV_KV + (kc * 64 + 32 + lane) * 16);
#pragma unroll
      for (int ks = 0; ks < 4; ks++) {
        const uint32_t b0 = b[ks >> 1][(ks & 1) * 2], b1 = b[ks >> 1][(ks & 1) * 2 + 1];
        mma16816((ks & 1) ? kw : kv, a[ks], b0, b1);
        if (FIRST) {
          const float f0 = bf_lo(a[ks][0]), f1 = bf_hi(a[ks][0]), f2 = bf_lo(a[ks][2]), f3 = bf_hi(a[ks][2]);
          const float h0 = bf_lo(a[ks][1]), h1 = bf_hi(a[ks][1]), h2 = bf_lo(a[ks][3]), h3 = bf_hi(a[ks][3]);
          rs0 += (f0 + f1) + (f2 + f3); rq0 += f0 * f0 + f1 * f1 + f2 * f2 + f3 * f3;
          rs1 += (h0 + h1) + (h2 + h3); rq1 += h0 * h0 + h1 * h1 + h2 * h2 + h3 * h3;
          const uint32_t one[4] = {0x3F803F80u, 0x3F803F80u, 0x3F803F80u, 0x3F803F80u};
          mma16816(ones, one, b0, b1);
        }
      }
    }
#pragma unroll
    for (int i = 0; i < 4; i++) kv[i] += kw[i];
    if (FIRST) {
#pragma unroll
      for (int o = 1; o < 4; o <<= 1) {
        rs0 += __shfl_xor_sync(~0u, rs0, o); rq0 += __shfl_xor_sync(~0u, rq0, o);
        rs1 += __shfl_xor_sync(~0u, rs1, o); rq1 += __shfl_xor_sync(~0u, rq1, o);
      }
      mean0 = rs0 * (1.f / D_); mean1 = rs1 * (1.f / D_);
      rstd0 = rsqrtf(fmaxf(rq0 * (1.f / D_) - mean0 * mean0, 0.f) + LN_EPS);
      rstd1 = rsqrtf(fmaxf(rq1 * (1.f / D_) - mean1 * mean1, 0.f) + LN_EPS);
      ck0 = ones[0]; ck1 = ones[1];
      if (t == 0) { s_mean[rl0] = mean0; s_rstd[rl0] = rstd0; s_mean[rl0 + 8] = mean1; s_rstd[rl0 + 8] = rstd1; }
      asm volatile("bar.arrive 1, 384;" ::: "memory");
      if (tb == 0 && w4 == 0 && g == 0) { g_csQKV[hg * 136 + 128 + 2 * t] = ck0; g_csQKV[hg * 136 + 128 + 2 * t + 1] = ck1; }
      if (hg == 0 && t1 == 0) {
#pragma unroll 1
        for (int kc = 0; kc < 8; kc++) bulk_s2g(g_x0T + (tb * 8 + kc) * 8192, sb + kc * QKV_CH, 8192);
        asm volatile("cp.async.bulk.commit_group;" ::: "memory");
      }
    }
    uint32_t u0 = pack_bf16((kv[0] - mean0 * ck0) * rstd0, (kv[1] - mean0 * ck1) * rstd0);
    uint32_t u1 = pack_bf16((kv[2] - mean1 * ck0) * rstd1, (kv[3] - mean1 * ck1) * rstd1);
    uint8_t* kvp = g_KV + (r0 >> 8) * 16384;
    const int kk = r0 & 255;
    if (hg < 2) {
      *reinterpret_cast<uint32_t*>(kvp + (kk >> 3) * 256 + hg * 128 + (kk & 7) * 16 + t * 4) = u0;
      *reinterpret_cast<uint32_t*>(kvp + ((kk + 8) >> 3) * 256 + hg * 128 + (kk & 7) * 16 + t * 4) = u1;
      float m0 = fmaxf(fabsf(bf_lo(u0)), fabsf(bf_lo(u1))), m1 = fmaxf(fabsf(bf_hi(u0)), fabsf(bf_hi(u1)));
      if (!(bf_lo(u0) == bf_lo(u0)) || !(bf_lo(u1) == bf_lo(u1))) m0 = __int_as_float(0x7f800000);
      if (!(bf_hi(u0) == bf_hi(u0)) || !(bf_hi(u1) == bf_hi(u1))) m1 = __int_as_float(0x7f800000);
#pragma unroll
      for (int o = 4; o < 32; o <<= 1) { m0 = fmaxf(m0, __shfl_xor_sync(~0u, m0, o)); m1 = fmaxf(m1, __shfl_xor_sync(~0u, m1, o)); }
      if (g == 0) { s_km[w4 * 8 + 2 * t] = m0; s_km[w4 * 8 + 2 * t + 1] = m1; }
      bar_sync(2, 128);
      if (t1 < 8) g_kmax[tb * 16 + hg * 8 + t1] = fmaxf(fmaxf(s_km[t1], s_km[8 + t1]), fmaxf(s_km[16 + t1], s_km[24 + t1]));
    } else {
      const uint32_t mask = ((r0 >> 6) & 1) ? LUT_MASK_ODD : LUT_MASK_EVEN;
      if ((mask >> ((r0 >> 3) & 7)) & 1) u0 ^= 0x80008000u;
      if ((mask >> (((r0 + 8) >> 3) & 7)) & 1) u1 ^= 0x80008000u;
      *reinterpret_cast<uint32_t*>(kvp + 8192 + (hg - 2) * 4096 + kk * 16 + t * 4) = u0;
      *reinterpret_cast<uint32_t*>(kvp + 8192 + (hg - 2) * 4096 + (kk + 8) * 16 + t * 4) = u1;
    }
    if (FIRST && hg == 0 && t1 == 0) asm volatile("cp.async.bulk.wait_group 0;" ::: "memory");
    return;
  }
  float acc[64];
#pragma unroll
  for (int i = 0; i < 64; i++) acc[i] = 0.f;
  fence_regs<64>(acc);
#pragma unroll 1
  for (int kc = 0; kc < 8; kc++) {
    const uint32_t st = sb + kc * QKV_CH;
    mbar_wait(bars + kc * 8, 0);
    if (tid == 0 && kc == 0) TS(KID, 1);
    wg_fence();
#pragma unroll
    for (int ks = 0; ks < 4; ks++)
      wgmma_ss_tb_n128(acc, mkdesc(st + ks * 32, 16, 1024, 1), mkdesc(st + 8192 + ks * 2048, 8192, 1024, 1), 1);
    wg_commit();
  }
  wg_wait<0>();
  fence_regs<64>(acc);
  if (tid == 0) TS(KID, 2);
  bar_sync(1, NSYNC);
  if (!FIRST) pdl_wait();
  if (tid == 0) TS(KID, 4);
  const int rl0 = warp * 16 + g;
  const float mean0 = s_mean[rl0], mean1 = s_mean[rl0 + 8];
  const float q0 = s_rstd[rl0] * QSCALE, q1 = s_rstd[rl0 + 8] * QSCALE;
  const uint32_t stg = sb + 8192;
  const int rl = warp * 16 + ((lane >> 3) & 1) * 8 + (lane & 7);
#pragma unroll
  for (int j = 0; j < 16; j += 2) {
    const float2 ca = *reinterpret_cast<const float2*>(s_cs + 8 * j + 2 * t);
    const float2 cb = *reinterpret_cast<const float2*>(s_cs + 8 * j + 8 + 2 * t);
    const float* a = acc + 4 * j;
    stsm4(stg + (j >> 3) * 8192 + rl * 128 + ((((j & 7) + (lane >> 4)) ^ (rl & 7)) << 4),
          pack_bf16((a[0] - mean0 * ca.x) * q0, (a[1] - mean0 * ca.y) * q0), pack_bf16((a[2] - mean1 * ca.x) * q1, (a[3] - mean1 * ca.y) * q1),
          pack_bf16((a[4] - mean0 * cb.x) * q0, (a[5] - mean0 * cb.y) * q0), pack_bf16((a[6] - mean1 * cb.x) * q1, (a[7] - mean1 * cb.y) * q1));
  }
  fence_async_smem();
  bar_sync(3, 128);
  if (tid == 0) {
    TS(KID, 6);
    bulk_s2g(g_QT + (tb * 8 + hg * 2) * 8192, stg, 16384);
    bulk_commit_wait_all();
    TS(KID, 3);
  }
}

constexpr int ATT_SMEM = 31 * 1024 + 192 * 1024 + 2048 + 1024;
constexpr int KVCH = 20480;
constexpr float LUT_MAGIC = 382.875f;

template <uint32_t MASK>
__device__ __forceinline__ void exp_pack(const float* s, uint32_t* p, uint32_t lutlane) {
#pragma unroll
  for (int i = 0; i < 16; i++) {
    if ((MASK >> (i / 2)) & 1) {
      const uint32_t b0 = __float_as_uint(s[2 * i] + LUT_MAGIC), b1 = __float_as_uint(s[2 * i + 1] + LUT_MAGIC);
      uint32_t c0, c1, w;
      asm volatile("ld.shared.u16 %0, [%1+2];" : "=r"(c0) : "r"((b0 & 0x7F80u) | lutlane));
      asm volatile("ld.shared.u32 %0, [%1];" : "=r"(c1) : "r"((b1 & 0x7F80u) | lutlane));
      asm("prmt.b32 %0, %1, %2, 0x6521;" : "=r"(w) : "r"(b0), "r"(b1));
      p[i] = w + c0 + c1;
    } else {
      p[i] = pack_bf16(ex2f(s[2 * i]), ex2f(s[2 * i + 1]));
    }
  }
}

__device__ __noinline__ void pack_weights(const CUtensorMap* mW1, const bf16* __restrict__ wo, const bf16* __restrict__ w2, int cta, uint8_t* smraw) {
  const int tid = threadIdx.x;
  const uint32_t sb = (smem_u32(smraw) + 1023) & ~1023u;
  uint8_t* sp = smraw + (sb - smem_u32(smraw));
  constexpr int IMG = 28672, NBUF = 7;
  const uint32_t bars = sb + NBUF * IMG;
  float* part = reinterpret_cast<float*>(sp + NBUF * IMG + 64);
  if (tid == 0) {
    for (int i = 0; i < NBUF; i++) mbar_init(bars + i * 8, 1);
    mbar_fence_init();
    for (int i = 0; i < NBUF; i++) { mbar_expect(bars + i * 8, IMG); tma3d(sb + i * IMG, mW1, 0, (i & 7) * 64, (cta * 2 + (i >> 3)) * 7, bars + i * 8); }
  }
  if (tid == 32) {
    constexpr uint32_t WO_B = D_ * D_ * 2 / NPACK, W2_B = F_ * D_ * 2 / NPACK;
    for (uint32_t o = 0; o < WO_B; o += 16384) asm volatile("cp.async.bulk.prefetch.L2.global [%0], %1;" ::"l"((const char*)wo + cta * WO_B + o), "r"(16384));
    for (uint32_t o = 0; o < W2_B; o += 16384) asm volatile("cp.async.bulk.prefetch.L2.global [%0], %1;" ::"l"((const char*)w2 + cta * W2_B + o), "r"(16384));
  }
  __syncthreads();
  const int cg = tid % 28, rg = tid / 28;
  float cs[8];
#pragma unroll
  for (int i = 0; i < 8; i++) cs[i] = 0.f;
#pragma unroll 1
  for (int it = 0; it < 16; it++) {
    const int buf = it % NBUF;
    mbar_wait(bars + buf * 8, (it / NBUF) & 1);
    if (tid == 0) { bulk_s2g(g_W1p + (size_t)(cta * 16 + it) * IMG, sb + buf * IMG, IMG); asm volatile("cp.async.bulk.commit_group;" ::: "memory"); }
    if (tid < 448) {
#pragma unroll
      for (int r = 0; r < 4; r++) {
        const int row = rg * 4 + r;
        const uint4 v = *reinterpret_cast<const uint4*>(sp + buf * IMG + (cg >> 2) * 4096 + row * 64 + (((cg & 3) ^ ((row >> 1) & 3)) << 4));
        cs[0] += bf_lo(v.x); cs[1] += bf_hi(v.x); cs[2] += bf_lo(v.y); cs[3] += bf_hi(v.y);
        cs[4] += bf_lo(v.z); cs[5] += bf_hi(v.z); cs[6] += bf_lo(v.w); cs[7] += bf_hi(v.w);
      }
    }
    if ((it & 7) == 7) {
      if (tid < 448) {
#pragma unroll
        for (int i = 0; i < 8; i++) { part[rg * 224 + cg * 8 + i] = cs[i]; cs[i] = 0.f; }
      }
      __syncthreads();
      if (tid < 224) {
        float s = 0.f;
#pragma unroll
        for (int q = 0; q < 16; q++) s += part[q * 224 + tid];
        g_cs1[(cta * 2 + (it >> 3)) * 224 + tid] = s;
      }
    }
    __syncthreads();
    if (tid == 0 && it + NBUF < 16) {
      asm volatile("cp.async.bulk.wait_group.read 0;" ::: "memory");
      const int nx = it + NBUF;
      mbar_expect(bars + buf * 8, IMG);
      tma3d(sb + buf * IMG, mW1, 0, (nx & 7) * 64, (cta * 2 + (nx >> 3)) * 7, bars + buf * 8);
    }
  }
  if (tid == 0) asm volatile("cp.async.bulk.wait_group 0;" ::: "memory");
  __threadfence();
  __syncthreads();
  if (tid == 0) asm volatile("red.release.gpu.global.add.u32 [%0], 1;" ::"l"(&g_pack_done) : "memory");
}

__global__ void __launch_bounds__(512, 1) attn_kernel(const __grid_constant__ CUtensorMap mW1, const bf16* __restrict__ wo, const bf16* __restrict__ w2, int KID) {
  extern __shared__ uint8_t smraw[];
  const uint32_t sbase = smem_u32(smraw);
  const uint32_t bars = sbase;
  const uint32_t kred = sbase + 128;
  const uint32_t qst = (sbase + 4096 + 1023) & ~1023u;
  const uint32_t LUT = (qst + 16384 + 32767) & ~32767u;
  const uint32_t KS = LUT + 32768;
  if (blockIdx.x >= 128) { pdl_trigger(); pack_weights(&mW1, wo, w2, blockIdx.x - 128, smraw); return; }
  uint8_t* sm0 = smraw - sbase;
  const int tid = threadIdx.x, lane = tid & 31, wg = tid >> 7, warp = (tid >> 5) & 3;
  if (tid == 0) TS(KID, 0);
  pdl_trigger();
  if (tid == 0) {
    for (int i = 0; i < 8; i++) mbar_init(bars + i * 8, 1);
    mbar_fence_init();
  }
  for (int i = tid; i < 256 * 32; i += 512) {
    const int idx = i >> 5;
    const float v = exp2f((idx + 0.5f) * (1.f / 256.f) + 0.125f);
    const int target = (v < 2.f) ? (int)rintf(128.f * v) - 128 : (int)rintf(64.f * v);
    reinterpret_cast<uint32_t*>(sm0 + LUT)[i] = (uint32_t)(target - (idx >> 1)) << 16;
  }
  for (int i = tid; i < S_; i += 512) {
    const uint32_t mask = ((i >> 6) & 1) ? LUT_MASK_ODD : LUT_MASK_EVEN;
    const uint32_t o = ((mask >> ((i >> 3) & 7)) & 1) ? 0xBF80BF80u : 0x3F803F80u;
    *reinterpret_cast<uint4*>(sm0 + KS + (i >> 8) * KVCH + 16384 + (i & 255) * 16) = make_uint4(o, o, o, o);
  }
  fence_async_smem();
  __syncthreads();
  if (tid == 0) TS(KID, 5);
  pdl_wait();
  if (tid == 0) TS(KID, 4);
  const int tb = blockIdx.x >> 2, hg = blockIdx.x & 3;
  if (tid == 0) {
    mbar_expect(bars, 16384 + 16384 + 2048);
    bulk_g2s(qst, g_QT + (tb * 8 + hg * 2) * 8192, 16384, bars);
    bulk_g2s(KS, g_KV, 16384, bars);
    bulk_g2s(kred, g_kmax, 2048, bars);
  } else if (tid == 128) {
    mbar_expect(bars + 8, 16384);
    bulk_g2s(KS + KVCH, g_KV + 16384, 16384, bars + 8);
  } else if (tid == 256) {
#pragma unroll 1
    for (int c = 2; c < 8; c++) {
      mbar_expect(bars + c * 8, 16384);
      bulk_g2s(KS + c * KVCH, g_KV + c * 16384, 16384, bars + c * 8);
    }
  }
  __syncwarp();
  const int g = lane >> 2, t = lane & 3;
  mbar_wait(bars, 0);
  if (tid == 0) TS(KID, 6);
  const uint32_t lutlane = LUT | (lane * 4);
  constexpr uint64_t KSTEP = (64 * 32) >> 4, VSTEP = (16 * 16) >> 4;
  constexpr uint64_t KJUMP = (KVCH - 3 * 2048) >> 4, VJUMP = (KVCH - 4096) >> 4;
#pragma unroll 1
  for (int tile = 0; tile < 2; tile++) {
    const int hl = wg * 2 + tile;
    const int arow = warp * 16 + (lane & 15);
    const uint32_t qaddr = qst + (hl >> 2) * 8192 + arow * 128 + ((((hl & 3) * 2 + (lane >> 4)) ^ (arow & 7)) << 4);
    uint32_t q[4];
    ldsm4(q, qaddr);
    float o[12];
#pragma unroll
    for (int i = 0; i < 12; i++) o[i] = 0.f;
    uint64_t kd = mkdesc(KS, 128, 256, 0);
    uint64_t vd = mkdesc(KS + 8192, 128, 4096, 0);
    {
      float s[32];
      uint32_t p[16];
      if (tid == 0 && tile == 0) TS(KID, 1);
      fence_regs<12>(o);
      wg_fence();
      wgmma_rs_n64(s, q[0], q[1], q[2], q[3], kd, 0); kd += KSTEP;
      wg_commit();
#pragma unroll 1
      for (int c = 0; c < 8; c++) {
        if (c < 7) mbar_wait(bars + (c + 1) * 8, 0);
#pragma unroll 1
        for (int j = 0; j < 2; j++) {
          wg_wait<0>(); fence_regs<32>(s); fence_regs<12>(o); fence_regs_u<16>(p);
          exp_pack<LUT_MASK_EVEN>(s, p, lutlane);
          wg_fence();
#pragma unroll
          for (int k = 0; k < 4; k++) { wgmma_rs_tb_n24(o, p[4 * k], p[4 * k + 1], p[4 * k + 2], p[4 * k + 3], vd, 1); vd += VSTEP; }
          wgmma_rs_n64(s, q[0], q[1], q[2], q[3], kd, 0); kd += j ? KJUMP : KSTEP;
          wg_commit();
          wg_wait<0>(); fence_regs<32>(s); fence_regs<12>(o); fence_regs_u<16>(p);
          exp_pack<LUT_MASK_ODD>(s, p, lutlane);
          wg_fence();
#pragma unroll
          for (int k = 0; k < 4; k++) { wgmma_rs_tb_n24(o, p[4 * k], p[4 * k + 1], p[4 * k + 2], p[4 * k + 3], vd, 1); vd += VSTEP; }
          wgmma_rs_n64(s, q[0], q[1], q[2], q[3], kd, 0); kd += KSTEP;
          wg_commit();
        }
        vd += VJUMP;
      }
      wg_wait<0>(); fence_regs<12>(o); fence_regs<32>(s);
    }
    uint32_t unsafe;
    {
      const float4* kr = reinterpret_cast<const float4*>(sm0 + kred);
      float4 m = kr[lane];
#pragma unroll
      for (int i = 1; i < 4; i++) {
        const float4 v = kr[lane + 32 * i];
        m.x = fmaxf(m.x, v.x); m.y = fmaxf(m.y, v.y); m.z = fmaxf(m.z, v.z); m.w = fmaxf(m.w, v.w);
      }
#pragma unroll
      for (int of = 4; of < 32; of <<= 1) {
        m.x = fmaxf(m.x, __shfl_xor_sync(~0u, m.x, of)); m.y = fmaxf(m.y, __shfl_xor_sync(~0u, m.y, of));
        m.z = fmaxf(m.z, __shfl_xor_sync(~0u, m.z, of)); m.w = fmaxf(m.w, __shfl_xor_sync(~0u, m.w, of));
      }
      const float ax = __shfl_sync(~0u, m.x, t >> 1), ay = __shfl_sync(~0u, m.y, t >> 1), az = __shfl_sync(~0u, m.z, t >> 1), aw = __shfl_sync(~0u, m.w, t >> 1);
      const float bx = __shfl_sync(~0u, m.x, 2 + (t >> 1)), by = __shfl_sync(~0u, m.y, 2 + (t >> 1)), bz = __shfl_sync(~0u, m.z, 2 + (t >> 1)),
                  bw = __shfl_sync(~0u, m.w, 2 + (t >> 1));
      const float k0 = (t & 1) ? az : ax, k1 = (t & 1) ? aw : ay, k2 = (t & 1) ? bz : bx, k3 = (t & 1) ? bw : by;
      float b0 = fabsf(bf_lo(q[0])) * k0 + fabsf(bf_hi(q[0])) * k1 + fabsf(bf_lo(q[2])) * k2 + fabsf(bf_hi(q[2])) * k3;
      float b1 = fabsf(bf_lo(q[1])) * k0 + fabsf(bf_hi(q[1])) * k1 + fabsf(bf_lo(q[3])) * k2 + fabsf(bf_hi(q[3])) * k3;
      b0 += __shfl_xor_sync(~0u, b0, 1); b0 += __shfl_xor_sync(~0u, b0, 2);
      b1 += __shfl_xor_sync(~0u, b1, 1); b1 += __shfl_xor_sync(~0u, b1, 2);
      unsafe = __any_sync(~0u, !(b0 <= SAFE_SCORE_BOUND && b1 <= SAFE_SCORE_BOUND)) ? 1u : 0u;
    }
    if (unsafe) {
#pragma unroll
      for (int i = 0; i < 12; i++) o[i] = 0.f;
      float m0 = -INFINITY, m1 = -INFINITY;
#pragma unroll 1
      for (int kb = 0; kb < S_ / 16; kb++) {
        uint32_t kf[4];
        float sa[4] = {0.f, 0.f, 0.f, 0.f}, sc[4] = {0.f, 0.f, 0.f, 0.f};
        ldsm4(kf, KS + (kb >> 4) * KVCH + (kb & 15) * 512 + lane * 16);
        mma16816(sa, q, kf[0], kf[1]);
        mma16816(sc, q, kf[2], kf[3]);
        m0 = fmaxf(fmaxf(m0, fmaxf(sa[0], sa[1])), fmaxf(sc[0], sc[1]));
        m1 = fmaxf(fmaxf(m1, fmaxf(sa[2], sa[3])), fmaxf(sc[2], sc[3]));
      }
      m0 = fmaxf(m0, __shfl_xor_sync(~0u, m0, 1)); m0 = fmaxf(m0, __shfl_xor_sync(~0u, m0, 2));
      m1 = fmaxf(m1, __shfl_xor_sync(~0u, m1, 1)); m1 = fmaxf(m1, __shfl_xor_sync(~0u, m1, 2));
#pragma unroll 1
      for (int kb = 0; kb < S_ / 16; kb++) {
        uint32_t kf[4], vf[4], ef[4], a[4];
        float sa[4] = {0.f, 0.f, 0.f, 0.f}, sc[4] = {0.f, 0.f, 0.f, 0.f};
        const uint32_t chb = KS + (kb >> 4) * KVCH;
        ldsm4(kf, chb + (kb & 15) * 512 + lane * 16);
        const uint32_t krow = chb + 8192 + ((kb & 15) * 16 + (lane & 15)) * 16;
        ldsm4t(vf, krow + (lane >> 4) * 4096);
        ldsm4t(ef, krow + 8192);
        mma16816(sa, q, kf[0], kf[1]);
        mma16816(sc, q, kf[2], kf[3]);
        const uint32_t mask = ((kb >> 2) & 1) ? LUT_MASK_ODD : LUT_MASK_EVEN;
        const uint32_t sg0 = ((mask >> ((2 * kb) & 7)) & 1) ? 0x80008000u : 0u, sg1 = ((mask >> ((2 * kb + 1) & 7)) & 1) ? 0x80008000u : 0u;
        a[0] = pack_bf16(ex2f(sa[0] - m0), ex2f(sa[1] - m0)) ^ sg0;
        a[1] = pack_bf16(ex2f(sa[2] - m1), ex2f(sa[3] - m1)) ^ sg0;
        a[2] = pack_bf16(ex2f(sc[0] - m0), ex2f(sc[1] - m0)) ^ sg1;
        a[3] = pack_bf16(ex2f(sc[2] - m1), ex2f(sc[3] - m1)) ^ sg1;
        mma16816(o, a, vf[0], vf[1]);
        mma16816(o + 4, a, vf[2], vf[3]);
        mma16816(o + 8, a, ef[0], ef[1]);
      }
    }
    const float r0 = 1.f / o[8], r1 = 1.f / o[10];
    stsm4(qst + (hl >> 2) * 8192 + (warp * 16 + ((lane >> 3) & 1) * 8 + (lane & 7)) * 128 +
              ((((hl & 3) * 2 + (lane >> 4)) ^ (lane & 7)) << 4),
          pack_bf16(o[0] * r0, o[1] * r0), pack_bf16(o[2] * r1, o[3] * r1), pack_bf16(o[4] * r0, o[5] * r0), pack_bf16(o[6] * r1, o[7] * r1));
    if (tid == 0 && tile == 0) TS(KID, 2);
  }
  fence_async_smem();
  __syncthreads();
  if (tid == 0) {
    bulk_s2g(g_OT + (tb * 8 + hg * 2) * 8192, qst, 16384);
    bulk_commit_wait_all();
    TS(KID, 3);
  }
}

__device__ __forceinline__ void residual_block(const float* a, uint32_t tile, int warp, int lane, float2* stat_out  ) {
  const int rl = warp * 16 + ((lane >> 3) & 1) * 8 + (lane & 7);
  const uint32_t rowa = tile + rl * 128;
  float s0 = 0.f, q0 = 0.f, s1 = 0.f, q1 = 0.f;
#pragma unroll
  for (int j = 0; j < 8; j += 2) {
    const uint32_t ad = rowa + (((j + (lane >> 4)) ^ (rl & 7)) << 4);
    uint32_t r[4];
    ldsm4(r, ad);
    const float* c = a + 4 * j;
    const uint32_t u0 = pack_bf16(bf_lo(r[0]) + c[0], bf_hi(r[0]) + c[1]);
    const uint32_t u1 = pack_bf16(bf_lo(r[1]) + c[2], bf_hi(r[1]) + c[3]);
    const uint32_t u2 = pack_bf16(bf_lo(r[2]) + c[4], bf_hi(r[2]) + c[5]);
    const uint32_t u3 = pack_bf16(bf_lo(r[3]) + c[6], bf_hi(r[3]) + c[7]);
    s0 += (bf_lo(u0) + bf_hi(u0)) + (bf_lo(u2) + bf_hi(u2));
    q0 += bf_lo(u0) * bf_lo(u0) + bf_hi(u0) * bf_hi(u0) + bf_lo(u2) * bf_lo(u2) + bf_hi(u2) * bf_hi(u2);
    s1 += (bf_lo(u1) + bf_hi(u1)) + (bf_lo(u3) + bf_hi(u3));
    q1 += bf_lo(u1) * bf_lo(u1) + bf_hi(u1) * bf_hi(u1) + bf_lo(u3) * bf_lo(u3) + bf_hi(u3) * bf_hi(u3);
    stsm4(ad, u0, u1, u2, u3);
  }
#pragma unroll
  for (int o = 1; o < 4; o <<= 1) {
    s0 += __shfl_xor_sync(~0u, s0, o); q0 += __shfl_xor_sync(~0u, q0, o);
    s1 += __shfl_xor_sync(~0u, s1, o); q1 += __shfl_xor_sync(~0u, q1, o);
  }
  if ((lane & 3) == 0) {
    stat_out[0] = make_float2(s0, q0);
    stat_out[8 * 8] = make_float2(s1, q1);
  }
}

constexpr int OPJ_CH = 8192 + 16384;
constexpr int OPJ_SMEM = 8 * OPJ_CH + 16384 + 1024 + 256;
__global__ void __launch_bounds__(192, 1) oproj_kernel(const __grid_constant__ CUtensorMap mW, const uint8_t* __restrict__ resT, int KID) {
  extern __shared__ uint8_t smraw[];
  const uint32_t sb = (smem_u32(smraw) + 1023) & ~1023u;
  const uint32_t res = sb + 8 * OPJ_CH, bars = res + 16384;
  const int tid = threadIdx.x, lane = tid & 31, warp = tid >> 5;
  const int tb = blockIdx.x >> 2, ct = blockIdx.x & 3;
  if (tid == 0) TS(KID, 0);
  pdl_trigger();
  if (tid == 0) {
    tmap_prefetch(&mW);
    for (int i = 0; i < 9; i++) mbar_init(bars + i * 8, 1);
    mbar_fence_init();
  }
  __syncthreads();
  if (tid == 128) {
#pragma unroll 1
    for (int kc = 0; kc < 8; kc++) {
      mbar_expect(bars + kc * 8, OPJ_CH);
      tma3d(sb + kc * OPJ_CH + 8192, &mW, 0, kc * 64, ct * 2, bars + kc * 8);
    }
  } else if (tid == 160) {
    TS(KID, 6);
    pdl_wait();
    TS(KID, 5);
#pragma unroll 1
    for (int kc = 0; kc < 8; kc++) bulk_g2s(sb + kc * OPJ_CH, g_OT + (tb * 8 + kc) * 8192, 8192, bars + kc * 8);
    mbar_expect(bars + 64, 16384);
    bulk_g2s(res, resT + (tb * 8 + ct * 2) * 8192, 16384, bars + 64);
  }
  if (warp >= 4) return;
  float acc[64];
#pragma unroll
  for (int i = 0; i < 64; i++) acc[i] = 0.f;
  fence_regs<64>(acc);
#pragma unroll 1
  for (int kc = 0; kc < 8; kc++) {
    const uint32_t st = sb + kc * OPJ_CH;
    mbar_wait(bars + kc * 8, 0);
    if (tid == 0 && kc == 0) TS(KID, 1);
    wg_fence();
#pragma unroll
    for (int ks = 0; ks < 4; ks++)
      wgmma_ss_tb_n128(acc, mkdesc(st + ks * 32, 16, 1024, 1), mkdesc(st + 8192 + ks * 2048, 8192, 1024, 1), 1);
    wg_commit();
  }
  wg_wait<0>();
  fence_regs<64>(acc);
  if (tid == 0) TS(KID, 2);
  pdl_wait();
  mbar_wait(bars + 64, 0);
  const int r0 = tb * 64 + warp * 16 + (lane >> 2);
  residual_block(acc, res, warp, lane, g_statB + r0 * 8 + ct * 2);
  residual_block(acc + 32, res + 8192, warp, lane, g_statB + r0 * 8 + ct * 2 + 1);
  fence_async_smem();
  bar_sync(1, 128);
  if (tid == 0) {
    bulk_s2g(g_x1T + (tb * 8 + ct * 2) * 8192, res, 16384);
    TS(KID, 4);
    bulk_commit_wait_all();
    TS(KID, 3);
  }
}

constexpr int F1_STAGES = 5, F1_A = 16384, F1_B = 28672, F1_STAGE = F1_A + F1_B;
constexpr int F1_AUX = F1_STAGES * F1_STAGE;
constexpr int F1_SMEM = F1_AUX + 128 + 480 * 4 + 1024;
__global__ void __launch_bounds__(320, 1) ffn1_kernel(int early, int KID) {
  extern __shared__ uint8_t smraw[];
  const uint32_t sb = (smem_u32(smraw) + 1023) & ~1023u;
  const uint32_t bars = sb + F1_AUX;
  float* s_mean = reinterpret_cast<float*>(smraw + (sb - smem_u32(smraw)) + F1_AUX + 128);
  float* s_rstd = s_mean + 128;
  float* s_cs = s_rstd + 128;
  const int tid = threadIdx.x, lane = tid & 31, warp = tid >> 5;
  const int mb = blockIdx.x >> 3, fs = blockIdx.x & 7;
  if (tid == 0) TS(KID, 0);
  pdl_trigger();
  if (tid == 0) {
    for (int i = 0; i < F1_STAGES; i++) { mbar_init(bars + i * 8, 1); mbar_init(bars + (F1_STAGES + i) * 8, 8); }
    mbar_fence_init();
  }
  __syncthreads();
  const uint8_t* gA = g_x1T + (size_t)mb * 2 * 65536;
  const uint8_t* gB = g_W1p + (size_t)fs * 8 * F1_B;
  constexpr int F1_PRE = 3;
  if (warp == 8) {
    if (lane == 0) {
      const bool pre = early || pack_ready();
      if (!pre) pdl_wait();
#pragma unroll 1
      for (int kc = 0; kc < F1_STAGES; kc++) {
        mbar_expect(bars + kc * 8, F1_STAGE);
        if (kc < F1_PRE) bulk_g2s(sb + kc * F1_STAGE + F1_A, gB + kc * F1_B, F1_B, bars + kc * 8);
      }
      TS(KID, 6);
      pdl_wait();
      TS(KID, 5);
#pragma unroll 1
      for (int kc = 0; kc < 8; kc++) {
        const int s = kc % F1_STAGES;
        const uint32_t fb = bars + s * 8, st = sb + s * F1_STAGE;
        if (kc >= F1_STAGES) {
          mbar_wait(bars + (F1_STAGES + s) * 8, 0);
          mbar_expect(fb, F1_STAGE);
        }
        bulk_g2s(st, gA + kc * 8192, 8192, fb);
        bulk_g2s(st + 8192, gA + 65536 + kc * 8192, 8192, fb);
        if (kc >= F1_PRE) bulk_g2s(st + F1_A, gB + kc * F1_B, F1_B, fb);
      }
    }
    return;
  }
  if (warp == 9) {
    pdl_wait();
#pragma unroll
    for (int i = 0; i < 4; i++) {
      float mean, rstd;
      row_stats(g_statB, mb * 128 + i * 32 + lane, mean, rstd);
      s_mean[i * 32 + lane] = mean; s_rstd[i * 32 + lane] = rstd;
    }
#pragma unroll
    for (int i = 0; i < 7; i++) s_cs[i * 32 + lane] = __ldcg(g_cs1 + fs * 224 + i * 32 + lane);
    asm volatile("bar.arrive 1, 288;" ::: "memory");
    return;
  }
  const int wg = warp >> 2, w4 = warp & 3;
  float acc[112];
#pragma unroll
  for (int i = 0; i < 112; i++) acc[i] = 0.f;
  fence_regs<112>(acc);
#pragma unroll 1
  for (int kc = 0; kc < 8; kc++) {
    const int s = kc % F1_STAGES;
    const uint32_t st = sb + s * F1_STAGE;
    mbar_wait(bars + s * 8, kc / F1_STAGES);
    if (tid == 0 && kc == 0) TS(KID, 1);
    wg_fence();
#pragma unroll
    for (int ks = 0; ks < 4; ks++)
      wgmma_ss_tb_n224(acc, mkdesc(st + wg * 8192 + ks * 32, 16, 1024, 1), mkdesc(st + F1_A + ks * 1024, 4096, 512, 2), 1);
    wg_commit();
    if (kc >= 1 && kc - 1 < 8 - F1_STAGES) {
      wg_wait<1>();
      if (lane == 0) mbar_arrive(bars + (F1_STAGES + kc - 1) * 8);
    }
  }
  wg_wait<0>();
  fence_regs<112>(acc);
  if (tid == 0) TS(KID, 2);
  pdl_wait();
  bar_sync(1, 288);
  const int g = lane >> 2, t = lane & 3;
  const int rl0 = wg * 64 + w4 * 16 + g;
  const float mean0 = s_mean[rl0], rstd0 = s_rstd[rl0], mean1 = s_mean[rl0 + 8], rstd1 = s_rstd[rl0 + 8];
  const uint32_t stg = sb + wg * 28672;
  const int rl = w4 * 16 + ((lane >> 3) & 1) * 8 + (lane & 7);
  constexpr float NL2E = -1.4426950408889634f;
#pragma unroll
  for (int j = 0; j < 28; j += 2) {
    const float2 ca = *reinterpret_cast<const float2*>(s_cs + 8 * j + 2 * t);
    const float2 cb = *reinterpret_cast<const float2*>(s_cs + 8 * j + 8 + 2 * t);
    const float* a = acc + 4 * j;
    float z[8];
    z[0] = (a[0] - mean0 * ca.x) * rstd0; z[1] = (a[1] - mean0 * ca.y) * rstd0;
    z[2] = (a[2] - mean1 * ca.x) * rstd1; z[3] = (a[3] - mean1 * ca.y) * rstd1;
    z[4] = (a[4] - mean0 * cb.x) * rstd0; z[5] = (a[5] - mean0 * cb.y) * rstd0;
    z[6] = (a[6] - mean1 * cb.x) * rstd1; z[7] = (a[7] - mean1 * cb.y) * rstd1;
#pragma unroll
    for (int i = 0; i < 8; i++) z[i] = __fdividef(z[i], 1.f + ex2f(z[i] * NL2E));
    const int blk = j >> 2, ch = (j & 3) + (lane >> 4);
    stsm4(stg + blk * 4096 + rl * 64 + ((ch ^ ((rl >> 1) & 3)) << 4), pack_bf16(z[0], z[1]), pack_bf16(z[2], z[3]), pack_bf16(z[4], z[5]),
          pack_bf16(z[6], z[7]));
    if (j == 10 || j == 18 || j == 26) {
      fence_async_smem();
      bar_sync(2 + wg, 128);
      if ((tid & 127) == 0) {
        const int b0 = j == 10 ? 0 : (j == 18 ? 3 : 5), nb = j == 10 ? 3 : 2;
        bulk_s2g(g_hT + ((size_t)(mb * 2 + wg) * 56 + fs * 7 + b0) * 4096, stg + b0 * 4096, nb * 4096);
        asm volatile("cp.async.bulk.commit_group;" ::: "memory");
      }
    }
  }
  if ((tid & 127) == 0) {
    if (tid == 0) TS(KID, 4);
    asm volatile("cp.async.bulk.wait_group 0;" ::: "memory");
    if (tid == 0) TS(KID, 3);
  }
}

constexpr int F2_STAGES = 5, F2_STAGE = 32768;
constexpr int F2_SMEM = F2_STAGES * F2_STAGE + 16384 + 32768 + 1024 + 256;
template <bool LAST>
__global__ void __cluster_dims__(2, 1, 1) __launch_bounds__(288, 1)
ffn2_kernel(const __grid_constant__ CUtensorMap mW, const __grid_constant__ CUtensorMap mOut, int KID) {
  extern __shared__ uint8_t smraw[];
  const uint32_t sb = (smem_u32(smraw) + 1023) & ~1023u;
  const uint32_t res = sb + F2_STAGES * F2_STAGE, recv = res + 16384, bars = recv + 32768;
  const int tid = threadIdx.x, lane = tid & 31, warp = tid >> 5;
  const int mb = blockIdx.x >> 3, nt = (blockIdx.x & 7) >> 1, kh = blockIdx.x & 1;
  if (tid == 0) TS(KID, 0);
  pdl_trigger();
  if (tid == 0) {
    tmap_prefetch(&mW);
    if (LAST) tmap_prefetch(&mOut);
    for (int i = 0; i < F2_STAGES; i++) { mbar_init(bars + i * 8, 1); mbar_init(bars + (F2_STAGES + i) * 8, 8); }
    mbar_init(bars + 2 * F2_STAGES * 8, 1);
    mbar_fence_init();
  }
  __syncthreads();
  const uint8_t* gA = g_hT + ((size_t)mb * 2 * 56 + kh * 28) * 4096;
  if (warp == 8) {
    if (lane == 0) {
#pragma unroll 1
      for (int kc = 0; kc < F2_STAGES; kc++) {
        mbar_expect(bars + kc * 8, F2_STAGE);
        tma3d(sb + kc * F2_STAGE + 16384, &mW, 0, kh * 896 + kc * 64, nt * 2, bars + kc * 8);
      }
      TS(KID, 6);
      pdl_wait();
      if (LAST && blockIdx.x == 0) g_pack_done = 0;
      int s = 0, ph = 0;
#pragma unroll 1
      for (int kc = 0; kc < 14; kc++) {
        const uint32_t fb = bars + s * 8, st = sb + s * F2_STAGE;
        if (kc >= F2_STAGES) {
          mbar_wait(bars + (F2_STAGES + s) * 8, ph);
          mbar_expect(fb, F2_STAGE);
        }
        bulk_g2s(st, gA + kc * 8192, 8192, fb);
        bulk_g2s(st + 8192, gA + 56 * 4096 + kc * 8192, 8192, fb);
        if (kc >= F2_STAGES) tma3d(st + 16384, &mW, 0, kh * 896 + kc * 64, nt * 2, fb);
        if (kc == F2_STAGES - 1) {
          const uint32_t rb = bars + 2 * F2_STAGES * 8;
          mbar_expect(rb, 16384);
          bulk_g2s(res, g_x1T + ((mb * 2) * 8 + nt * 2 + kh) * 8192, 8192, rb);
          bulk_g2s(res + 8192, g_x1T + ((mb * 2 + 1) * 8 + nt * 2 + kh) * 8192, 8192, rb);
        }
        if (++s == F2_STAGES) { s = 0; if (kc >= F2_STAGES) ph ^= 1; }
      }
    }
    return;
  }
  const int wg = warp >> 2, w4 = warp & 3;
  float acc[64];
#pragma unroll
  for (int i = 0; i < 64; i++) acc[i] = 0.f;
  fence_regs<64>(acc);
  {
    int s = 0, ph = 0, ps = 0;
#pragma unroll 1
    for (int kc = 0; kc < 14; kc++) {
      const uint32_t st = sb + s * F2_STAGE;
      mbar_wait(bars + s * 8, ph);
      if (tid == 0 && kc == 0) TS(KID, 1);
      wg_fence();
#pragma unroll
      for (int ks = 0; ks < 4; ks++)
        wgmma_ss_tb_n128(acc, mkdesc(st + wg * 8192 + (ks >> 1) * 4096 + (ks & 1) * 32, 16, 512, 2), mkdesc(st + 16384 + ks * 2048, 8192, 1024, 1), 1);
      wg_commit();
      if (kc >= 1) {
        wg_wait<1>();
        if (lane == 0) mbar_arrive(bars + (F2_STAGES + ps) * 8);
      }
      ps = s;
      if (++s == F2_STAGES) { s = 0; ph ^= 1; }
    }
  }
  wg_wait<0>();
  fence_regs<64>(acc);
  if (tid == 0) TS(KID, 2);
  {
    uint32_t dst;
    asm volatile("mapa.shared::cluster.u32 %0, %1, %2;" : "=r"(dst) : "r"(recv + wg * 16384 + (tid & 127) * 16), "r"(kh ^ 1));
#pragma unroll
    for (int i = 0; i < 8; i++) {
      const float x0 = kh ? acc[4 * i] : acc[32 + 4 * i], x1 = kh ? acc[4 * i + 1] : acc[33 + 4 * i];
      const float x2 = kh ? acc[4 * i + 2] : acc[34 + 4 * i], x3 = kh ? acc[4 * i + 3] : acc[35 + 4 * i];
      asm volatile("st.shared::cluster.v4.f32 [%0], {%1,%2,%3,%4};" ::"r"(dst + i * 2048), "f"(x0), "f"(x1), "f"(x2), "f"(x3) : "memory");
    }
  }
  asm volatile("barrier.cluster.arrive.release.aligned;" ::: "memory");
  asm volatile("barrier.cluster.wait.acquire.aligned;" ::: "memory");
  if (tid == 0) TS(KID, 5);
  float fin[32];
#pragma unroll
  for (int i = 0; i < 8; i++) {
    float4 v;
    asm volatile("ld.shared.v4.f32 {%0,%1,%2,%3}, [%4];" : "=f"(v.x), "=f"(v.y), "=f"(v.z), "=f"(v.w) : "r"(recv + wg * 16384 + (tid & 127) * 16 + i * 2048));
    fin[4 * i] = v.x + (kh ? acc[32 + 4 * i] : acc[4 * i]);
    fin[4 * i + 1] = v.y + (kh ? acc[33 + 4 * i] : acc[4 * i + 1]);
    fin[4 * i + 2] = v.z + (kh ? acc[34 + 4 * i] : acc[4 * i + 2]);
    fin[4 * i + 3] = v.w + (kh ? acc[35 + 4 * i] : acc[4 * i + 3]);
  }
  pdl_wait();
  mbar_wait(bars + 2 * F2_STAGES * 8, 0);
  const int r0 = mb * 128 + wg * 64 + w4 * 16 + (lane >> 2);
  residual_block(fin, res + wg * 8192, w4, lane, g_statA + r0 * 8 + nt * 2 + kh);
  fence_async_smem();
  bar_sync(2 + wg, 128);
  if ((tid & 127) == 0) {
    if (LAST) tma2d_store(&mOut, nt * 128 + kh * 64, mb * 128 + wg * 64, res + wg * 8192);
    else bulk_s2g(g_x2T + ((mb * 2 + wg) * 8 + nt * 2 + kh) * 8192, res + wg * 8192, 8192);
    if (tid == 0) TS(KID, 4);
    bulk_commit_wait_all();
    if (tid == 0) TS(KID, 3);
    if (LAST && tid == 0 && blockIdx.x == 0) GT(1);
  }
}

typedef CUresult (*EncodeFn)(CUtensorMap*, CUtensorMapDataType, cuuint32_t, void*, const cuuint64_t*, const cuuint64_t*, const cuuint32_t*,
                             const cuuint32_t*, CUtensorMapInterleave, CUtensorMapSwizzle, CUtensorMapL2promotion, CUtensorMapFloatOOBfill);

CUtensorMap make_map(EncodeFn fn, const void* base, int rank, const cuuint64_t* dims, const cuuint64_t* strides, const cuuint32_t* box,
                     CUtensorMapSwizzle swz) {
  CUtensorMap m;
  cuuint32_t es[3] = {1, 1, 1};
  fn(&m, CU_TENSOR_MAP_DATA_TYPE_BFLOAT16, rank, const_cast<void*>(base), dims, strides, box, es, CU_TENSOR_MAP_INTERLEAVE_NONE, swz,
     CU_TENSOR_MAP_L2_PROMOTION_NONE, CU_TENSOR_MAP_FLOAT_OOB_FILL_NONE);
  return m;
}
CUtensorMap map2d(EncodeFn fn, const void* base, int rows, int cols, int box_rows) {
  cuuint64_t dims[2] = {(cuuint64_t)cols, (cuuint64_t)rows}, strides[1] = {(cuuint64_t)cols * 2};
  cuuint32_t box[2] = {64, (cuuint32_t)box_rows};
  return make_map(fn, base, 2, dims, strides, box, CU_TENSOR_MAP_SWIZZLE_128B);
}
CUtensorMap map3d(EncodeFn fn, const void* base, int rows, int cols, int inner, int box_rows, int box_blocks) {
  cuuint64_t dims[3] = {(cuuint64_t)inner, (cuuint64_t)rows, (cuuint64_t)(cols / inner)};
  cuuint64_t strides[2] = {(cuuint64_t)cols * 2, (cuuint64_t)inner * 2};
  cuuint32_t box[3] = {(cuuint32_t)inner, (cuuint32_t)box_rows, (cuuint32_t)box_blocks};
  return make_map(fn, base, 3, dims, strides, box, inner == 64 ? CU_TENSOR_MAP_SWIZZLE_128B : CU_TENSOR_MAP_SWIZZLE_64B);
}

template <typename... KArgs, typename... Args>
void launch(void (*kern)(KArgs...), int grid, int block, int smem, bool pdl, Args... args) {
  cudaLaunchConfig_t cfg = {};
  cfg.gridDim = dim3(grid);
  cfg.blockDim = dim3(block);
  cfg.dynamicSmemBytes = smem;
  cfg.stream = cudaStreamPerThread;
  cudaLaunchAttribute at[1];
  at[0].id = cudaLaunchAttributeProgrammaticStreamSerialization;
  at[0].val.programmaticStreamSerializationAllowed = 1;
  cfg.attrs = at;
  cfg.numAttrs = pdl ? 1 : 0;
  cudaLaunchKernelEx(&cfg, kern, args...);
}

}

extern "C" void kernel_launch(void* const* d_in, const int* in_sizes, int n_in, void* d_out, int out_size) {
  const bf16* x = (const bf16*)d_in[0];
  const bf16* wq = (const bf16*)d_in[1];
  const bf16* wk = (const bf16*)d_in[2];
  const bf16* wv = (const bf16*)d_in[3];
  const bf16* wo = (const bf16*)d_in[4];
  const bf16* w1 = (const bf16*)d_in[6];
  const bf16* w2 = (const bf16*)d_in[7];

  void* fp = nullptr;
  cudaDriverEntryPointQueryResult qr;
  cudaGetDriverEntryPoint("cuTensorMapEncodeTiled", &fp, cudaEnableDefault, &qr);
  EncodeFn fn = (EncodeFn)fp;
  const CUtensorMap mOut = map2d(fn, d_out, S_, D_, 64), mX = map2d(fn, x, S_, D_, 64);
  const CUtensorMap mWq = map3d(fn, wq, D_, D_, 64, 64, 2), mWo = map3d(fn, wo, D_, D_, 64, 64, 2);
  const CUtensorMap mW1 = map3d(fn, w1, D_, F_, 32, 64, 7), mW2 = map3d(fn, w2, F_, D_, 64, 64, 2);

  cudaFuncSetAttribute(qkv_kernel<true>, cudaFuncAttributeMaxDynamicSharedMemorySize, QKV_SMEM);
  cudaFuncSetAttribute(qkv_kernel<false>, cudaFuncAttributeMaxDynamicSharedMemorySize, QKV_SMEM);
  cudaFuncSetAttribute(attn_kernel, cudaFuncAttributeMaxDynamicSharedMemorySize, ATT_SMEM);
  cudaFuncSetAttribute(oproj_kernel, cudaFuncAttributeMaxDynamicSharedMemorySize, OPJ_SMEM);
  cudaFuncSetAttribute(ffn1_kernel, cudaFuncAttributeMaxDynamicSharedMemorySize, F1_SMEM);
  cudaFuncSetAttribute(ffn2_kernel<false>, cudaFuncAttributeMaxDynamicSharedMemorySize, F2_SMEM);
  cudaFuncSetAttribute(ffn2_kernel<true>, cudaFuncAttributeMaxDynamicSharedMemorySize, F2_SMEM);
  void *pX0T, *pX2T;
  cudaGetSymbolAddress(&pX0T, g_x0T);
  cudaGetSymbolAddress(&pX2T, g_x2T);

  for (int layer = 0; layer < 2; layer++) {
    if (layer == 0) launch(qkv_kernel<true>, 128, 384, QKV_SMEM, false, mX, mWq, wk, wv);
    else launch(qkv_kernel<false>, 128, 256, QKV_SMEM, true, mX, mWq, wk, wv);
    launch(attn_kernel, layer == 0 ? 128 + (int)NPACK : 128, 512, ATT_SMEM, true, mW1, wo, w2, 2 + layer * 5);
    launch(oproj_kernel, 128, 192, OPJ_SMEM, true, mWo, (const uint8_t*)(layer == 0 ? pX0T : pX2T), 3 + layer * 5);
    launch(ffn1_kernel, 128, 320, F1_SMEM, true, layer, 4 + layer * 5);
    if (layer == 0) launch(ffn2_kernel<false>, 128, 288, F2_SMEM, true, mW2, mOut, 5 + layer * 5);
    else launch(ffn2_kernel<true>, 128, 288, F2_SMEM, true, mW2, mOut, 5 + layer * 5);
  }
}
```

```cpp
#include <cuda_runtime.h>
#include <cuda_bf16.h>
#include <cuda.h>
#include <stdint.h>

namespace {

typedef __nv_bfloat16 bf16;
constexpr int S_ = 2048, D_ = 512, F_ = 1792;
constexpr float LN_EPS = 1e-5f;
constexpr float QSCALE = 0.25f * 1.4426950408889634f;

constexpr uint32_t LUT_MASK_EVEN = 0x55, LUT_MASK_ODD = 0x55;
constexpr float SAFE_SCORE_BOUND = 80.0f;

__device__ __align__(1024) uint4 g_x0F[S_ * D_ / 8];
__device__ __align__(1024) uint4 g_QF[S_ * D_ / 8];
__device__ __align__(1024) uint4 g_OF[S_ * D_ / 8];
__device__ __align__(1024) uint4 g_x1F[S_ * D_ / 8];
__device__ __align__(1024) uint4 g_x2F[S_ * D_ / 8];
__device__ __align__(1024) uint4 g_hF[S_ * F_ / 8];
__device__ __align__(1024) uint8_t g_KV[S_ * 64];
__device__ __align__(1024) float g_kmax[32 * 16];
__device__ __align__(1024) float2 g_statA[8 * S_];
__device__ __align__(1024) float2 g_statB[S_ * 8];
__device__ __align__(1024) float g_csQKV[4 * 136];
__device__ __align__(1024) float g_cs1[F_];
__device__ __align__(1024) uint8_t g_W1p[8 * 8 * 28672];
constexpr unsigned NPACK = 4;
enum { F_X1 = 0  , F_H = 16  , F_X2 = 48  , F_CS = 64  , F_COUNT = 68 };
__device__ __align__(1024) unsigned g_flags[F_COUNT * 32];

__device__ __forceinline__ uint32_t smem_u32(const void* p) { return (uint32_t)__cvta_generic_to_shared(p); }
__device__ __forceinline__ void mbar_init(uint32_t b, uint32_t c) { asm volatile("mbarrier.init.shared::cta.b64 [%0], %1;" ::"r"(b), "r"(c)); }
__device__ __forceinline__ void mbar_fence_init() { asm volatile("fence.mbarrier_init.release.cluster;" ::: "memory"); }
__device__ __forceinline__ void mbar_expect(uint32_t b, uint32_t bytes) {
  asm volatile("mbarrier.arrive.expect_tx.shared::cta.b64 _, [%0], %1;" ::"r"(b), "r"(bytes) : "memory");
}
__device__ __forceinline__ void mbar_arrive(uint32_t b) { asm volatile("mbarrier.arrive.shared::cta.b64 _, [%0];" ::"r"(b) : "memory"); }
__device__ __forceinline__ void mbar_wait(uint32_t b, uint32_t ph) {
  asm volatile(
      "{.reg .pred p; .reg .u32 n;\n"
      "mov.u32 n, 0;\n"
      "LAB_WAIT:\n"
      "mbarrier.try_wait.parity.shared::cta.b64 p, [%0], %1;\n"
      "add.u32 n, n, 1;\n"
      "setp.ge.or.u32 p, n, 0x40000, p;\n"
      "@!p bra LAB_WAIT;\n}" ::"r"(b), "r"(ph) : "memory");
}
__device__ __forceinline__ void mbar_wait_cluster(uint32_t b, uint32_t ph) {
  asm volatile(
      "{.reg .pred p; .reg .u32 n;\n"
      "mov.u32 n, 0;\n"
      "LAB_WAIT:\n"
      "mbarrier.try_wait.parity.acquire.cluster.shared::cta.b64 p, [%0], %1;\n"
      "add.u32 n, n, 1;\n"
      "setp.ge.or.u32 p, n, 0x40000, p;\n"
      "@!p bra LAB_WAIT;\n}" ::"r"(b), "r"(ph) : "memory");
}
__device__ __forceinline__ void bulk_g2s(uint32_t dst, const void* src, uint32_t bytes, uint32_t bar) {
  asm volatile("cp.async.bulk.shared::cluster.global.mbarrier::complete_tx::bytes [%0], [%1], %2, [%3];" ::"r"(dst), "l"(src), "r"(bytes), "r"(bar) : "memory");
}
__device__ __forceinline__ void bulk_s2g(void* dst, uint32_t src, uint32_t bytes) {
  asm volatile("cp.async.bulk.global.shared::cta.bulk_group [%0], [%1], %2;" ::"l"(dst), "r"(src), "r"(bytes) : "memory");
}
__device__ __forceinline__ void flag_arrive(int f) {
  asm volatile("red.release.gpu.global.add.u32 [%0], 1;" ::"l"(&g_flags[f * 32]) : "memory");
}
__device__ __forceinline__ void flag_wait(int f, unsigned target) {
  const unsigned* p = &g_flags[f * 32];
  unsigned v, it = 0;
  do {
    asm volatile("ld.acquire.gpu.global.u32 %0, [%1];" : "=r"(v) : "l"(p) : "memory");
  } while (v < target && ++it < (1u << 22));
  asm volatile("fence.proxy.async.global;" ::: "memory");
}
__device__ __forceinline__ void tma2d(uint32_t dst, const CUtensorMap* m, int c0, int c1, uint32_t bar) {
  asm volatile("cp.async.bulk.tensor.2d.shared::cluster.global.mbarrier::complete_tx::bytes [%0], [%1, {%3, %4}], [%2];"
               ::"r"(dst), "l"(m), "r"(bar), "r"(c0), "r"(c1) : "memory");
}
__device__ __forceinline__ void tma3d(uint32_t dst, const CUtensorMap* m, int c0, int c1, int c2, uint32_t bar) {
  asm volatile("cp.async.bulk.tensor.3d.shared::cluster.global.mbarrier::complete_tx::bytes [%0], [%1, {%3, %4, %5}], [%2];"
               ::"r"(dst), "l"(m), "r"(bar), "r"(c0), "r"(c1), "r"(c2) : "memory");
}
__device__ __forceinline__ void tmap_prefetch(const CUtensorMap* m) { asm volatile("prefetch.tensormap [%0];" ::"l"(m) : "memory"); }
__device__ __forceinline__ void tma2d_store(const CUtensorMap* m, int c0, int c1, uint32_t src) {
  asm volatile("cp.async.bulk.tensor.2d.global.shared::cta.bulk_group [%0, {%2, %3}], [%1];" ::"l"(m), "r"(src), "r"(c0), "r"(c1) : "memory");
}
__device__ __forceinline__ void bulk_commit_wait_all() {
  asm volatile("cp.async.bulk.commit_group;" ::: "memory");
  asm volatile("cp.async.bulk.wait_group 0;" ::: "memory");
}
__device__ __forceinline__ void fence_async_smem() { asm volatile("fence.proxy.async.shared::cta;" ::: "memory"); }
__device__ __forceinline__ void pdl_trigger() { asm volatile("griddepcontrol.launch_dependents;" ::: "memory"); }
__device__ __forceinline__ void pdl_wait() { asm volatile("griddepcontrol.wait;" ::: "memory"); }
__device__ __forceinline__ void bar_sync(int id, int n) { asm volatile("bar.sync %0, %1;" ::"r"(id), "r"(n) : "memory"); }
__device__ __forceinline__ void wg_fence() { asm volatile("wgmma.fence.sync.aligned;" ::: "memory"); }
__device__ __forceinline__ void wg_commit() { asm volatile("wgmma.commit_group.sync.aligned;" ::: "memory"); }
template <int N> __device__ __forceinline__ void wg_wait() { asm volatile("wgmma.wait_group.sync.aligned %0;" ::"n"(N) : "memory"); }
__device__ __forceinline__ uint64_t mkdesc(uint32_t addr, uint32_t lbo, uint32_t sbo, uint32_t swz) {
  return (uint64_t)((addr & 0x3FFFF) >> 4) | ((uint64_t)(lbo >> 4) << 16) | ((uint64_t)(sbo >> 4) << 32) | ((uint64_t)swz << 62);
}
template <int N> __device__ __forceinline__ void fence_regs(float* d) {
#pragma unroll
  for (int i = 0; i < N; i++) asm volatile("" : "+f"(d[i])::"memory");
}
template <int N> __device__ __forceinline__ void fence_regs_u(uint32_t* d) {
#pragma unroll
  for (int i = 0; i < N; i++) asm volatile("" : "+r"(d[i])::"memory");
}
__device__ __forceinline__ uint32_t pack_bf16(float lo, float hi) {
  uint32_t r;
  asm("cvt.rn.bf16x2.f32 %0, %1, %2;" : "=r"(r) : "f"(hi), "f"(lo));
  return r;
}
__device__ __forceinline__ float bf_lo(uint32_t u) { return __uint_as_float(u << 16); }
__device__ __forceinline__ float bf_hi(uint32_t u) { return __uint_as_float(u & 0xFFFF0000u); }
__device__ __forceinline__ float ex2f(float x) {
  float y;
  asm("ex2.approx.ftz.f32 %0, %1;" : "=f"(y) : "f"(x));
  return y;
}
__device__ __forceinline__ void stsm4(uint32_t a, uint32_t r0, uint32_t r1, uint32_t r2, uint32_t r3) {
  asm volatile("stmatrix.sync.aligned.m8n8.x4.shared.b16 [%0], {%1,%2,%3,%4};" ::"r"(a), "r"(r0), "r"(r1), "r"(r2), "r"(r3));
}
__device__ __forceinline__ void ldsm4(uint32_t* r, uint32_t a) {
  asm volatile("ldmatrix.sync.aligned.m8n8.x4.shared.b16 {%0,%1,%2,%3}, [%4];" : "=r"(r[0]), "=r"(r[1]), "=r"(r[2]), "=r"(r[3]) : "r"(a) : "memory");
}
__device__ __forceinline__ void ldsm4t(uint32_t* r, uint32_t a) {
  asm volatile("ldmatrix.sync.aligned.m8n8.x4.trans.shared.b16 {%0,%1,%2,%3}, [%4];" : "=r"(r[0]), "=r"(r[1]), "=r"(r[2]), "=r"(r[3]) : "r"(a) : "memory");
}
__device__ __forceinline__ void mma16816(float* d, const uint32_t* a, uint32_t b0, uint32_t b1) {
  asm volatile("mma.sync.aligned.m16n8k16.row.col.f32.bf16.bf16.f32 {%0,%1,%2,%3}, {%4,%5,%6,%7}, {%8,%9}, {%0,%1,%2,%3};"
               : "+f"(d[0]), "+f"(d[1]), "+f"(d[2]), "+f"(d[3]) : "r"(a[0]), "r"(a[1]), "r"(a[2]), "r"(a[3]), "r"(b0), "r"(b1));
}
__device__ __forceinline__ void row_stats(const float2* __restrict__ st, int row, float& mean, float& rstd) {
  float s = 0.f, q = 0.f;
#pragma unroll
  for (int i = 0; i < 8; i++) {
    const float2 v = __ldcg(st + i * S_ + row);
    s += v.x;
    q += v.y;
  }
  mean = s * (1.f / D_);
  float var = fmaxf(q * (1.f / D_) - mean * mean, 0.f);
  rstd = rsqrtf(var + LN_EPS);
}

__device__ __forceinline__ void wgmma_rs_n64(float* d, uint32_t a0, uint32_t a1, uint32_t a2, uint32_t a3, uint64_t descB, int scaleD){
  asm volatile("{.reg .pred p; setp.ne.b32 p, %37, 0; wgmma.mma_async.sync.aligned.m64n64k16.f32.bf16.bf16 {%0,%1,%2,%3,%4,%5,%6,%7,%8,%9,%10,%11,%12,%13,%14,%15,%16,%17,%18,%19,%20,%21,%22,%23,%24,%25,%26,%27,%28,%29,%30,%31}, {%32,%33,%34,%35}, %36, p, 1, 1, 0;}"
   : "+f"(d[0]),"+f"(d[1]),"+f"(d[2]),"+f"(d[3]),"+f"(d[4]),"+f"(d[5]),"+f"(d[6]),"+f"(d[7]),"+f"(d[8]),"+f"(d[9]),"+f"(d[10]),"+f"(d[11]),"+f"(d[12]),"+f"(d[13]),"+f"(d[14]),"+f"(d[15]),"+f"(d[16]),"+f"(d[17]),"+f"(d[18]),"+f"(d[19]),"+f"(d[20]),"+f"(d[21]),"+f"(d[22]),"+f"(d[23]),"+f"(d[24]),"+f"(d[25]),"+f"(d[26]),"+f"(d[27]),"+f"(d[28]),"+f"(d[29]),"+f"(d[30]),"+f"(d[31])
   : "r"(a0),"r"(a1),"r"(a2),"r"(a3),"l"(descB),"r"(scaleD));
}

__device__ __forceinline__ void wgmma_rs_tb_n24(float* d, uint32_t a0, uint32_t a1, uint32_t a2, uint32_t a3, uint64_t descB, int scaleD){
  asm volatile("{.reg .pred p; setp.ne.b32 p, %17, 0; wgmma.mma_async.sync.aligned.m64n24k16.f32.bf16.bf16 {%0,%1,%2,%3,%4,%5,%6,%7,%8,%9,%10,%11}, {%12,%13,%14,%15}, %16, p, 1, 1, 1;}"
   : "+f"(d[0]),"+f"(d[1]),"+f"(d[2]),"+f"(d[3]),"+f"(d[4]),"+f"(d[5]),"+f"(d[6]),"+f"(d[7]),"+f"(d[8]),"+f"(d[9]),"+f"(d[10]),"+f"(d[11])
   : "r"(a0),"r"(a1),"r"(a2),"r"(a3),"l"(descB),"r"(scaleD));
}

__device__ __forceinline__ void wgmma_rs_tb_n128(float* d, uint32_t a0, uint32_t a1, uint32_t a2, uint32_t a3, uint64_t descB, int scaleD){
  asm volatile("{.reg .pred p; setp.ne.b32 p, %69, 0; wgmma.mma_async.sync.aligned.m64n128k16.f32.bf16.bf16 {%0,%1,%2,%3,%4,%5,%6,%7,%8,%9,%10,%11,%12,%13,%14,%15,%16,%17,%18,%19,%20,%21,%22,%23,%24,%25,%26,%27,%28,%29,%30,%31,%32,%33,%34,%35,%36,%37,%38,%39,%40,%41,%42,%43,%44,%45,%46,%47,%48,%49,%50,%51,%52,%53,%54,%55,%56,%57,%58,%59,%60,%61,%62,%63}, {%64,%65,%66,%67}, %68, p, 1, 1, 1;}"
   : "+f"(d[0]),"+f"(d[1]),"+f"(d[2]),"+f"(d[3]),"+f"(d[4]),"+f"(d[5]),"+f"(d[6]),"+f"(d[7]),"+f"(d[8]),"+f"(d[9]),"+f"(d[10]),"+f"(d[11]),"+f"(d[12]),"+f"(d[13]),"+f"(d[14]),"+f"(d[15]),"+f"(d[16]),"+f"(d[17]),"+f"(d[18]),"+f"(d[19]),"+f"(d[20]),"+f"(d[21]),"+f"(d[22]),"+f"(d[23]),"+f"(d[24]),"+f"(d[25]),"+f"(d[26]),"+f"(d[27]),"+f"(d[28]),"+f"(d[29]),"+f"(d[30]),"+f"(d[31]),"+f"(d[32]),"+f"(d[33]),"+f"(d[34]),"+f"(d[35]),"+f"(d[36]),"+f"(d[37]),"+f"(d[38]),"+f"(d[39]),"+f"(d[40]),"+f"(d[41]),"+f"(d[42]),"+f"(d[43]),"+f"(d[44]),"+f"(d[45]),"+f"(d[46]),"+f"(d[47]),"+f"(d[48]),"+f"(d[49]),"+f"(d[50]),"+f"(d[51]),"+f"(d[52]),"+f"(d[53]),"+f"(d[54]),"+f"(d[55]),"+f"(d[56]),"+f"(d[57]),"+f"(d[58]),"+f"(d[59]),"+f"(d[60]),"+f"(d[61]),"+f"(d[62]),"+f"(d[63])
   : "r"(a0),"r"(a1),"r"(a2),"r"(a3),"l"(descB),"r"(scaleD));
}

__device__ __forceinline__ void wgmma_rs_tb_n224(float* d, uint32_t a0, uint32_t a1, uint32_t a2, uint32_t a3, uint64_t descB, int scaleD){
  asm volatile("{.reg .pred p; setp.ne.b32 p, %117, 0; wgmma.mma_async.sync.aligned.m64n224k16.f32.bf16.bf16 {%0,%1,%2,%3,%4,%5,%6,%7,%8,%9,%10,%11,%12,%13,%14,%15,%16,%17,%18,%19,%20,%21,%22,%23,%24,%25,%26,%27,%28,%29,%30,%31,%32,%33,%34,%35,%36,%37,%38,%39,%40,%41,%42,%43,%44,%45,%46,%47,%48,%49,%50,%51,%52,%53,%54,%55,%56,%57,%58,%59,%60,%61,%62,%63,%64,%65,%66,%67,%68,%69,%70,%71,%72,%73,%74,%75,%76,%77,%78,%79,%80,%81,%82,%83,%84,%85,%86,%87,%88,%89,%90,%91,%92,%93,%94,%95,%96,%97,%98,%99,%100,%101,%102,%103,%104,%105,%106,%107,%108,%109,%110,%111}, {%112,%113,%114,%115}, %116, p, 1, 1, 1;}"
   : "+f"(d[0]),"+f"(d[1]),"+f"(d[2]),"+f"(d[3]),"+f"(d[4]),"+f"(d[5]),"+f"(d[6]),"+f"(d[7]),"+f"(d[8]),"+f"(d[9]),"+f"(d[10]),"+f"(d[11]),"+f"(d[12]),"+f"(d[13]),"+f"(d[14]),"+f"(d[15]),"+f"(d[16]),"+f"(d[17]),"+f"(d[18]),"+f"(d[19]),"+f"(d[20]),"+f"(d[21]),"+f"(d[22]),"+f"(d[23]),"+f"(d[24]),"+f"(d[25]),"+f"(d[26]),"+f"(d[27]),"+f"(d[28]),"+f"(d[29]),"+f"(d[30]),"+f"(d[31]),"+f"(d[32]),"+f"(d[33]),"+f"(d[34]),"+f"(d[35]),"+f"(d[36]),"+f"(d[37]),"+f"(d[38]),"+f"(d[39]),"+f"(d[40]),"+f"(d[41]),"+f"(d[42]),"+f"(d[43]),"+f"(d[44]),"+f"(d[45]),"+f"(d[46]),"+f"(d[47]),"+f"(d[48]),"+f"(d[49]),"+f"(d[50]),"+f"(d[51]),"+f"(d[52]),"+f"(d[53]),"+f"(d[54]),"+f"(d[55]),"+f"(d[56]),"+f"(d[57]),"+f"(d[58]),"+f"(d[59]),"+f"(d[60]),"+f"(d[61]),"+f"(d[62]),"+f"(d[63]),"+f"(d[64]),"+f"(d[65]),"+f"(d[66]),"+f"(d[67]),"+f"(d[68]),"+f"(d[69]),"+f"(d[70]),"+f"(d[71]),"+f"(d[72]),"+f"(d[73]),"+f"(d[74]),"+f"(d[75]),"+f"(d[76]),"+f"(d[77]),"+f"(d[78]),"+f"(d[79]),"+f"(d[80]),"+f"(d[81]),"+f"(d[82]),"+f"(d[83]),"+f"(d[84]),"+f"(d[85]),"+f"(d[86]),"+f"(d[87]),"+f"(d[88]),"+f"(d[89]),"+f"(d[90]),"+f"(d[91]),"+f"(d[92]),"+f"(d[93]),"+f"(d[94]),"+f"(d[95]),"+f"(d[96]),"+f"(d[97]),"+f"(d[98]),"+f"(d[99]),"+f"(d[100]),"+f"(d[101]),"+f"(d[102]),"+f"(d[103]),"+f"(d[104]),"+f"(d[105]),"+f"(d[106]),"+f"(d[107]),"+f"(d[108]),"+f"(d[109]),"+f"(d[110]),"+f"(d[111])
   : "r"(a0),"r"(a1),"r"(a2),"r"(a3),"l"(descB),"r"(scaleD));
}

__device__ __forceinline__ void wgmma_rs_tb_n8(float* d, uint32_t a0, uint32_t a1, uint32_t a2, uint32_t a3, uint64_t descB, int scaleD){
  asm volatile("{.reg .pred p; setp.ne.b32 p, %9, 0; wgmma.mma_async.sync.aligned.m64n8k16.f32.bf16.bf16 {%0,%1,%2,%3}, {%4,%5,%6,%7}, %8, p, 1, 1, 1;}"
   : "+f"(d[0]),"+f"(d[1]),"+f"(d[2]),"+f"(d[3])
   : "r"(a0),"r"(a1),"r"(a2),"r"(a3),"l"(descB),"r"(scaleD));
}

__device__ __forceinline__ void wgmma_ss_tb_n8(float* d, uint64_t descA, uint64_t descB, int scaleD){
  asm volatile("{.reg .pred p; setp.ne.b32 p, %6, 0; wgmma.mma_async.sync.aligned.m64n8k16.f32.bf16.bf16 {%0,%1,%2,%3}, %4, %5, p, 1, 1, 0, 1;}"
   : "+f"(d[0]),"+f"(d[1]),"+f"(d[2]),"+f"(d[3])
   : "l"(descA),"l"(descB),"r"(scaleD));
}

__device__ __forceinline__ void wgmma_ss_tb_n128(float* d, uint64_t descA, uint64_t descB, int scaleD){
  asm volatile("{.reg .pred p; setp.ne.b32 p, %66, 0; wgmma.mma_async.sync.aligned.m64n128k16.f32.bf16.bf16 {%0,%1,%2,%3,%4,%5,%6,%7,%8,%9,%10,%11,%12,%13,%14,%15,%16,%17,%18,%19,%20,%21,%22,%23,%24,%25,%26,%27,%28,%29,%30,%31,%32,%33,%34,%35,%36,%37,%38,%39,%40,%41,%42,%43,%44,%45,%46,%47,%48,%49,%50,%51,%52,%53,%54,%55,%56,%57,%58,%59,%60,%61,%62,%63}, %64, %65, p, 1, 1, 0, 1;}"
   : "+f"(d[0]),"+f"(d[1]),"+f"(d[2]),"+f"(d[3]),"+f"(d[4]),"+f"(d[5]),"+f"(d[6]),"+f"(d[7]),"+f"(d[8]),"+f"(d[9]),"+f"(d[10]),"+f"(d[11]),"+f"(d[12]),"+f"(d[13]),"+f"(d[14]),"+f"(d[15]),"+f"(d[16]),"+f"(d[17]),"+f"(d[18]),"+f"(d[19]),"+f"(d[20]),"+f"(d[21]),"+f"(d[22]),"+f"(d[23]),"+f"(d[24]),"+f"(d[25]),"+f"(d[26]),"+f"(d[27]),"+f"(d[28]),"+f"(d[29]),"+f"(d[30]),"+f"(d[31]),"+f"(d[32]),"+f"(d[33]),"+f"(d[34]),"+f"(d[35]),"+f"(d[36]),"+f"(d[37]),"+f"(d[38]),"+f"(d[39]),"+f"(d[40]),"+f"(d[41]),"+f"(d[42]),"+f"(d[43]),"+f"(d[44]),"+f"(d[45]),"+f"(d[46]),"+f"(d[47]),"+f"(d[48]),"+f"(d[49]),"+f"(d[50]),"+f"(d[51]),"+f"(d[52]),"+f"(d[53]),"+f"(d[54]),"+f"(d[55]),"+f"(d[56]),"+f"(d[57]),"+f"(d[58]),"+f"(d[59]),"+f"(d[60]),"+f"(d[61]),"+f"(d[62]),"+f"(d[63])
   : "l"(descA),"l"(descB),"r"(scaleD));
}

__device__ __forceinline__ void kv_epilogue(const float* kv, float mean0, float rstd0, float mean1, float rstd1, float ck0, float ck1, float* s_km,
                                            int tb, int hg, int r0, int rl0, int w4, int lane, int t1, int bar) {
  const int g = lane >> 2, t = lane & 3;
  uint32_t u0 = pack_bf16((kv[0] - mean0 * ck0) * rstd0, (kv[1] - mean0 * ck1) * rstd0);
  uint32_t u1 = pack_bf16((kv[2] - mean1 * ck0) * rstd1, (kv[3] - mean1 * ck1) * rstd1);
  uint8_t* dst = g_KV + (tb >> 2) * 16384 + (hg < 2 ? (tb & 3) * 2048 + hg * 1024 : 8192 + (hg - 2) * 4096 + (tb & 3) * 1024) + rl0 * 16 + t * 4;
  if (hg < 2) {
    float m0 = fmaxf(fabsf(bf_lo(u0)), fabsf(bf_lo(u1))), m1 = fmaxf(fabsf(bf_hi(u0)), fabsf(bf_hi(u1)));
    if (!(bf_lo(u0) == bf_lo(u0)) || !(bf_lo(u1) == bf_lo(u1))) m0 = __int_as_float(0x7f800000);
    if (!(bf_hi(u0) == bf_hi(u0)) || !(bf_hi(u1) == bf_hi(u1))) m1 = __int_as_float(0x7f800000);
#pragma unroll
    for (int o = 4; o < 32; o <<= 1) { m0 = fmaxf(m0, __shfl_xor_sync(~0u, m0, o)); m1 = fmaxf(m1, __shfl_xor_sync(~0u, m1, o)); }
    if (g == 0) { s_km[w4 * 8 + 2 * t] = m0; s_km[w4 * 8 + 2 * t + 1] = m1; }
  } else {
    const uint32_t mask = ((r0 >> 6) & 1) ? LUT_MASK_ODD : LUT_MASK_EVEN;
    if ((mask >> ((r0 >> 3) & 7)) & 1) u0 ^= 0x80008000u;
    if ((mask >> (((r0 + 8) >> 3) & 7)) & 1) u1 ^= 0x80008000u;
  }
  *reinterpret_cast<uint32_t*>(dst) = u0;
  *reinterpret_cast<uint32_t*>(dst + 128) = u1;
  bar_sync(bar, 128);
  if (hg < 2) {
    if (t1 < 8) g_kmax[tb * 16 + hg * 8 + t1] = fmaxf(fmaxf(s_km[t1], s_km[8 + t1]), fmaxf(s_km[16 + t1], s_km[24 + t1]));
    __syncwarp();
  }
}

__device__ __forceinline__ void q_epilogue(const float* acc, const float* s_mean, const float* s_rstd, const float* s_cs, int tb, int hg, int w4, int lane) {
  const int g = lane >> 2, t = lane & 3, rl0 = w4 * 16 + g;
  const float mean0 = s_mean[rl0], mean1 = s_mean[rl0 + 8];
  const float q0 = s_rstd[rl0] * QSCALE, q1 = s_rstd[rl0 + 8] * QSCALE;
  uint4* gq = g_QF + ((size_t)tb * 32 + hg * 8) * 128 + w4 * 32 + lane;
#pragma unroll
  for (int h = 0; h < 8; h++) {
    const float2 ca = *reinterpret_cast<const float2*>(s_cs + 16 * h + 2 * t);
    const float2 cb = *reinterpret_cast<const float2*>(s_cs + 16 * h + 8 + 2 * t);
    const float* a = acc + 8 * h;
    gq[h * 128] = make_uint4(pack_bf16((a[0] - mean0 * ca.x) * q0, (a[1] - mean0 * ca.y) * q0), pack_bf16((a[2] - mean1 * ca.x) * q1, (a[3] - mean1 * ca.y) * q1),
                             pack_bf16((a[4] - mean0 * cb.x) * q0, (a[5] - mean0 * cb.y) * q0), pack_bf16((a[6] - mean1 * cb.x) * q1, (a[7] - mean1 * cb.y) * q1));
  }
}

constexpr int QKV_CH = 8192 + 16384;
constexpr int QKV_KV = 8 * QKV_CH;
constexpr int QKV_AUX = QKV_KV + 8192;
constexpr int QKV_SMEM = QKV_AUX + 2048 + 1024;

__global__ void __launch_bounds__(384, 1) qkv_kernel(const __grid_constant__ CUtensorMap mX, const __grid_constant__ CUtensorMap mWq,
                                                      const bf16* __restrict__ wk, const bf16* __restrict__ wv) {
  extern __shared__ uint8_t smraw[];
  const uint32_t sb = (smem_u32(smraw) + 1023) & ~1023u;
  uint8_t* sp = smraw + (sb - smem_u32(smraw));
  float* s_mean = reinterpret_cast<float*>(sp + QKV_AUX);
  float* s_rstd = s_mean + 64;
  float* s_cs = s_rstd + 64;
  float* s_km = s_cs + 128;
  const uint32_t bars = sb + QKV_AUX + 1536;
  const int tid = threadIdx.x, lane = tid & 31, warp = tid >> 5;
  const int bid = (int)blockIdx.x - 4;
  const int tb = bid >> 2, hg = bid & 3;
  pdl_trigger();
  if (tid == 0) {
    tmap_prefetch(&mWq);
    tmap_prefetch(&mX);
    for (int i = 0; i < 8; i++) mbar_init(bars + i * 8, 1);
    mbar_fence_init();
  }
  __syncthreads();
  if (bid < 0) {
    const int h4 = blockIdx.x;
    if (lane == 0 && warp < 8) {
      mbar_expect(bars + warp * 8, 16384);
      tma3d(sb + warp * 16384, &mWq, 0, warp * 64, h4 * 2, bars + warp * 8);
    }
    __syncwarp();
    const int cg = (tid >> 3) & 15, kr = tid & 7, part = tid >> 7;
    float cs[8];
#pragma unroll
    for (int i = 0; i < 8; i++) cs[i] = 0.f;
#pragma unroll 1
    for (int kc = 0; kc < 8; kc++) {
      mbar_wait(bars + kc * 8, 0);
      const uint8_t* bp = sp + kc * 16384 + (cg >> 3) * 8192 + kr * 128 + (((cg & 7) ^ kr) << 4);
      for (int kg = part; kg < 8; kg += 3) {
        const uint4 v = *reinterpret_cast<const uint4*>(bp + kg * 1024);
        cs[0] += bf_lo(v.x); cs[1] += bf_hi(v.x); cs[2] += bf_lo(v.y); cs[3] += bf_hi(v.y);
        cs[4] += bf_lo(v.z); cs[5] += bf_hi(v.z); cs[6] += bf_lo(v.w); cs[7] += bf_hi(v.w);
      }
    }
#pragma unroll
    for (int i = 0; i < 8; i++) {
#pragma unroll
      for (int o = 1; o < 8; o <<= 1) cs[i] += __shfl_xor_sync(~0u, cs[i], o);
    }
    float* red = reinterpret_cast<float*>(sp + 8 * 16384);
    if (kr == 0) {
#pragma unroll
      for (int i = 0; i < 8; i++) red[part * 128 + cg * 8 + i] = cs[i];
    }
    __syncthreads();
    if (tid < 128) g_csQKV[h4 * 136 + tid] = red[tid] + red[128 + tid] + red[256 + tid];
    __syncthreads();
    if (tid == 0) flag_arrive(F_CS + h4);
    return;
  }
  if (tid == 128) {
#pragma unroll 1
    for (int kc = 0; kc < 8; kc++) {
      mbar_expect(bars + kc * 8, QKV_CH);
      tma3d(sb + kc * QKV_CH + 8192, &mWq, 0, kc * 64, hg * 2, bars + kc * 8);
    }
  } else if (tid == 160) {
#pragma unroll 1
    for (int kc = 0; kc < 8; kc++) tma2d(sb + kc * QKV_CH, &mX, kc * 64, tb * 64, bars + kc * 8);
  }
  __syncwarp();
  const int g = lane >> 2, t = lane & 3;
  if (warp >= 8) {
    const int t1 = tid & 127, w4 = warp & 3;
    float rs0 = 0.f, rq0 = 0.f, rs1 = 0.f, rq1 = 0.f;
    const int arow = w4 * 16 + (lane & 15);
#pragma unroll 1
    for (int kc = 0; kc < 8; kc++) {
      mbar_wait(bars + kc * 8, 0);
      const uint32_t st = sb + kc * QKV_CH;
#pragma unroll
      for (int ks = 0; ks < 4; ks++) {
        uint32_t a[4];
        ldsm4(a, st + arow * 128 + (((ks * 2 + (lane >> 4)) ^ (arow & 7)) << 4));
        if (hg == 0) g_x0F[((size_t)tb * 32 + kc * 4 + ks) * 128 + t1] = make_uint4(a[0], a[1], a[2], a[3]);
        const float f0 = bf_lo(a[0]), f1 = bf_hi(a[0]), f2 = bf_lo(a[2]), f3 = bf_hi(a[2]);
        const float h0 = bf_lo(a[1]), h1 = bf_hi(a[1]), h2 = bf_lo(a[3]), h3 = bf_hi(a[3]);
        rs0 += (f0 + f1) + (f2 + f3); rq0 += f0 * f0 + f1 * f1 + f2 * f2 + f3 * f3;
        rs1 += (h0 + h1) + (h2 + h3); rq1 += h0 * h0 + h1 * h1 + h2 * h2 + h3 * h3;
      }
    }
#pragma unroll
    for (int o = 1; o < 4; o <<= 1) {
      rs0 += __shfl_xor_sync(~0u, rs0, o); rq0 += __shfl_xor_sync(~0u, rq0, o);
      rs1 += __shfl_xor_sync(~0u, rs1, o); rq1 += __shfl_xor_sync(~0u, rq1, o);
    }
    if (t == 0) {
      const int rl0 = w4 * 16 + g;
      const float mean0 = rs0 * (1.f / D_), mean1 = rs1 * (1.f / D_);
      s_mean[rl0] = mean0; s_rstd[rl0] = rsqrtf(fmaxf(rq0 * (1.f / D_) - mean0 * mean0, 0.f) + LN_EPS);
      s_mean[rl0 + 8] = mean1; s_rstd[rl0 + 8] = rsqrtf(fmaxf(rq1 * (1.f / D_) - mean1 * mean1, 0.f) + LN_EPS);
    }
    asm volatile("bar.arrive 5, 256;" ::: "memory");
    if (lane == 0) flag_wait(F_CS + hg, 1);
    __syncwarp();
    s_cs[t1] = __ldcg(g_csQKV + hg * 136 + t1);
    asm volatile("bar.arrive 1, 256;" ::: "memory");
    return;
  }
  if (warp >= 4) {
    const int t1 = tid & 127, w4 = warp & 3;
    const bf16* wkv = (hg < 2 ? wk : wv) + (hg & 1) * 8;
    float ckq[8];
    {
      uint4 v[4];
#pragma unroll
      for (int i = 0; i < 4; i++) v[i] = __ldg(reinterpret_cast<const uint4*>(wkv + (size_t)(i * 128 + t1) * 16));
#pragma unroll
      for (int i = 0; i < 4; i++) *reinterpret_cast<uint4*>(sp + QKV_KV + (i * 128 + t1) * 16) = v[i];
#pragma unroll
      for (int i = 0; i < 8; i++) ckq[i] = 0.f;
#pragma unroll
      for (int i = 0; i < 4; i++) {
        ckq[0] += bf_lo(v[i].x); ckq[1] += bf_hi(v[i].x); ckq[2] += bf_lo(v[i].y); ckq[3] += bf_hi(v[i].y);
        ckq[4] += bf_lo(v[i].z); ckq[5] += bf_hi(v[i].z); ckq[6] += bf_lo(v[i].w); ckq[7] += bf_hi(v[i].w);
      }
      fence_async_smem();
    }
    float mean0, rstd0, mean1, rstd1, ck0, ck1;
    const int rl0 = w4 * 16 + g, r0 = tb * 64 + rl0;
    bar_sync(2, 128);
    float kv[4] = {0.f, 0.f, 0.f, 0.f};
    fence_regs<4>(kv);
#pragma unroll 1
    for (int kc = 0; kc < 8; kc++) {
      mbar_wait(bars + kc * 8, 0);
      const uint32_t st = sb + kc * QKV_CH;
      wg_fence();
#pragma unroll
      for (int ks = 0; ks < 4; ks++)
        wgmma_ss_tb_n8(kv, mkdesc(st + ks * 32, 16, 1024, 1), mkdesc(sb + QKV_KV + kc * 1024 + ks * 256, 128, 128, 0), 1);
      wg_commit();
    }
#pragma unroll
    for (int i = 0; i < 8; i++) {
#pragma unroll
      for (int o = 1; o < 32; o <<= 1) ckq[i] += __shfl_xor_sync(~0u, ckq[i], o);
    }
    if (lane == 0) {
#pragma unroll
      for (int i = 0; i < 8; i++) s_km[32 + w4 * 8 + i] = ckq[i];
    }
    bar_sync(2, 128);
    ck0 = s_km[32 + 2 * t] + s_km[40 + 2 * t] + s_km[48 + 2 * t] + s_km[56 + 2 * t];
    ck1 = s_km[33 + 2 * t] + s_km[41 + 2 * t] + s_km[49 + 2 * t] + s_km[57 + 2 * t];
    wg_wait<0>();
    fence_regs<4>(kv);
    if (tb == 0 && w4 == 0 && g == 0) { g_csQKV[hg * 136 + 128 + 2 * t] = ck0; g_csQKV[hg * 136 + 128 + 2 * t + 1] = ck1; }
    bar_sync(5, 256);
    mean0 = s_mean[rl0]; rstd0 = s_rstd[rl0]; mean1 = s_mean[rl0 + 8]; rstd1 = s_rstd[rl0 + 8];
    kv_epilogue(kv, mean0, rstd0, mean1, rstd1, ck0, ck1, s_km, tb, hg, r0, rl0, w4, lane, t1, 2);
    return;
  }
  float acc[64];
#pragma unroll
  for (int i = 0; i < 64; i++) acc[i] = 0.f;
  fence_regs<64>(acc);
#pragma unroll 1
  for (int kc = 0; kc < 8; kc++) {
    const uint32_t st = sb + kc * QKV_CH;
    mbar_wait(bars + kc * 8, 0);
    wg_fence();
#pragma unroll
    for (int ks = 0; ks < 4; ks++)
      wgmma_ss_tb_n128(acc, mkdesc(st + ks * 32, 16, 1024, 1), mkdesc(st + 8192 + ks * 2048, 8192, 1024, 1), 1);
    wg_commit();
  }
  wg_wait<0>();
  fence_regs<64>(acc);
  bar_sync(1, 256);
  q_epilogue(acc, s_mean, s_rstd, s_cs, tb, hg, warp, lane);
}

constexpr int ATT_SMEM = 31 * 1024 + 192 * 1024 + 2048 + 1024;
constexpr int KVCH = 20480;
constexpr float LUT_MAGIC = 382.875f;

template <uint32_t MASK, int I0 = 0, int I1 = 16>
__device__ __forceinline__ void exp_pack(const float* s, uint32_t* p, uint32_t lutlane) {
#pragma unroll
  for (int i = I0; i < I1; i++) {
    if ((MASK >> (i / 2)) & 1) {
      const uint32_t b0 = __float_as_uint(s[2 * i] + LUT_MAGIC), b1 = __float_as_uint(s[2 * i + 1] + LUT_MAGIC);
      uint32_t c0, c1, w;
      asm volatile("ld.shared.u16 %0, [%1+2];" : "=r"(c0) : "r"((b0 & 0x7F80u) | lutlane));
      asm volatile("ld.shared.u32 %0, [%1];" : "=r"(c1) : "r"((b1 & 0x7F80u) | lutlane));
      asm("prmt.b32 %0, %1, %2, 0x6521;" : "=r"(w) : "r"(b0), "r"(b1));
      p[i] = w + c0 + c1;
    } else {
      p[i] = pack_bf16(ex2f(s[2 * i]), ex2f(s[2 * i + 1]));
    }
  }
}

__device__ __noinline__ void pack_weights(const CUtensorMap* mW1, const bf16* __restrict__ wo, const bf16* __restrict__ w2, int cta, uint8_t* smraw) {
  const int tid = threadIdx.x;
  const uint32_t sb = (smem_u32(smraw) + 1023) & ~1023u;
  uint8_t* sp = smraw + (sb - smem_u32(smraw));
  constexpr int IMG = 28672, NBUF = 7;
  const uint32_t bars = sb + NBUF * IMG;
  float* part = reinterpret_cast<float*>(sp + NBUF * IMG + 64);
  if (tid == 0) {
    for (int i = 0; i < NBUF; i++) mbar_init(bars + i * 8, 1);
    mbar_fence_init();
    for (int i = 0; i < NBUF; i++) { mbar_expect(bars + i * 8, IMG); tma3d(sb + i * IMG, mW1, 0, (i & 7) * 64, (cta * 2 + (i >> 3)) * 7, bars + i * 8); }
  }
  if (tid == 32) {
    constexpr uint32_t WO_B = D_ * D_ * 2 / NPACK, W2_B = F_ * D_ * 2 / NPACK;
    for (uint32_t o = 0; o < WO_B; o += 16384) asm volatile("cp.async.bulk.prefetch.L2.global [%0], %1;" ::"l"((const char*)wo + cta * WO_B + o), "r"(16384));
    for (uint32_t o = 0; o < W2_B; o += 16384) asm volatile("cp.async.bulk.prefetch.L2.global [%0], %1;" ::"l"((const char*)w2 + cta * W2_B + o), "r"(16384));
  }
  __syncthreads();
  const int cg = tid % 28, rg = tid / 28;
  float cs[8];
#pragma unroll
  for (int i = 0; i < 8; i++) cs[i] = 0.f;
#pragma unroll 1
  for (int it = 0; it < 16; it++) {
    const int buf = it % NBUF;
    mbar_wait(bars + buf * 8, (it / NBUF) & 1);
    if (tid == 0) { bulk_s2g(g_W1p + (size_t)(cta * 16 + it) * IMG, sb + buf * IMG, IMG); asm volatile("cp.async.bulk.commit_group;" ::: "memory"); }
    if (tid < 448) {
#pragma unroll
      for (int r = 0; r < 4; r++) {
        const int row = rg * 4 + r;
        const uint4 v = *reinterpret_cast<const uint4*>(sp + buf * IMG + (cg >> 2) * 4096 + row * 64 + (((cg & 3) ^ ((row >> 1) & 3)) << 4));
        cs[0] += bf_lo(v.x); cs[1] += bf_hi(v.x); cs[2] += bf_lo(v.y); cs[3] += bf_hi(v.y);
        cs[4] += bf_lo(v.z); cs[5] += bf_hi(v.z); cs[6] += bf_lo(v.w); cs[7] += bf_hi(v.w);
      }
    }
    if ((it & 7) == 7) {
      if (tid < 448) {
#pragma unroll
        for (int i = 0; i < 8; i++) { part[rg * 224 + cg * 8 + i] = cs[i]; cs[i] = 0.f; }
      }
      __syncthreads();
      if (tid < 224) {
        float s = 0.f;
#pragma unroll
        for (int q = 0; q < 16; q++) s += part[q * 224 + tid];
        g_cs1[(cta * 2 + (it >> 3)) * 224 + tid] = s;
      }
    }
    __syncthreads();
    if (tid == 0 && it + NBUF < 16) {
      asm volatile("cp.async.bulk.wait_group.read 0;" ::: "memory");
      const int nx = it + NBUF;
      mbar_expect(bars + buf * 8, IMG);
      tma3d(sb + buf * IMG, mW1, 0, (nx & 7) * 64, (cta * 2 + (nx >> 3)) * 7, bars + buf * 8);
    }
  }
  if (tid == 0) asm volatile("cp.async.bulk.wait_group 0;" ::: "memory");
}

#define ATT_BLOCK(MASK, KNEXT)                                                     \
  wg_wait<0>(); fence_regs<32>(s); fence_regs<12>(o); fence_regs_u<16>(p);         \
  exp_pack<MASK, 0, 8>(s, p, lutlane);                                             \
  wg_fence();                                                                      \
  wgmma_rs_tb_n24(o, p[0], p[1], p[2], p[3], vd, 1); vd += VSTEP;                  \
  wgmma_rs_tb_n24(o, p[4], p[5], p[6], p[7], vd, 1); vd += VSTEP;                  \
  exp_pack<MASK, 8, 16>(s, p, lutlane);                                            \
  wg_fence();                                                                      \
  wgmma_rs_tb_n24(o, p[8], p[9], p[10], p[11], vd, 1); vd += VSTEP;                \
  wgmma_rs_tb_n24(o, p[12], p[13], p[14], p[15], vd, 1); vd += VSTEP;              \
  wgmma_rs_n64(s, q[0], q[1], q[2], q[3], kd, 0); kd += (KNEXT);                   \
  wg_commit();

__global__ void __launch_bounds__(512, 1) attn_kernel(const __grid_constant__ CUtensorMap mW1, const bf16* __restrict__ wo, const bf16* __restrict__ w2) {
  extern __shared__ uint8_t smraw[];
  const uint32_t sbase = smem_u32(smraw);
  const uint32_t bars = sbase;
  const uint32_t kred = sbase + 128;
  const uint32_t LUT = (sbase + 4096 + 32767) & ~32767u;
  const uint32_t KS = LUT + 32768;
  if (blockIdx.x >= 128) { pdl_trigger(); pack_weights(&mW1, wo, w2, blockIdx.x - 128, smraw); return; }
  uint8_t* sm0 = smraw - sbase;
  const int tid = threadIdx.x, lane = tid & 31, wg = tid >> 7;
  const int tb = blockIdx.x >> 2, hg = blockIdx.x & 3;
  const int c0 = (blockIdx.x >> 2) & 7;
  pdl_trigger();
  const bool issuer = (tid & 127) == 0 && tid < 384;
  if (tid == 32) {
    for (int i = 0; i < 8; i++) mbar_init(bars + i * 8, 1);
    mbar_fence_init();
  }
  {
    const int idx = (tid >> 5) * 16 + (lane & 15);
    const float v = exp2f((idx + 0.5f) * (1.f / 256.f) + 0.125f);
    const int target = (v < 2.f) ? (int)rintf(128.f * v) - 128 : (int)rintf(64.f * v);
    const uint32_t e = (uint32_t)(target - (idx >> 1)) << 16;
#pragma unroll
    for (int i = 0; i < 16; i++)
      reinterpret_cast<uint32_t*>(sm0 + LUT)[((tid >> 5) * 16 + i) * 32 + lane] = __shfl_sync(~0u, e, i);
  }
#pragma unroll
  for (int k = 0; k < 4; k++) {
    const int i = k * 512 + tid;
    const uint32_t mask = ((i >> 6) & 1) ? LUT_MASK_ODD : LUT_MASK_EVEN;
    const uint32_t o = ((mask >> ((i >> 3) & 7)) & 1) ? 0xBF80BF80u : 0x3F803F80u;
    *reinterpret_cast<uint4*>(sm0 + KS + (i >> 8) * KVCH + 16384 + (i & 255) * 16) = make_uint4(o, o, o, o);
  }
  fence_async_smem();
  __syncthreads();
  if (issuer) {
    pdl_wait();
    if (tid == 0) {
      mbar_expect(bars, 16384 + 2048);
      bulk_g2s(KS, g_KV + c0 * 16384, 16384, bars);
      bulk_g2s(kred, g_kmax, 2048, bars);
    } else if (tid == 128) {
      mbar_expect(bars + 8, 16384);
      bulk_g2s(KS + KVCH, g_KV + ((c0 + 1) & 7) * 16384, 16384, bars + 8);
    } else {
#pragma unroll 1
      for (int i = 2; i < 8; i++) {
        mbar_expect(bars + i * 8, 16384);
        bulk_g2s(KS + i * KVCH, g_KV + ((c0 + i) & 7) * 16384, 16384, bars + i * 8);
      }
    }
  }
  if (tid == 384 && blockIdx.x == 0) {
    pdl_wait();
    for (int i = 0; i < F_COUNT; i++) g_flags[i * 32] = 0;
  }
  __syncwarp();
  const int t = lane & 3;
  pdl_wait();
  const uint4 qf0 = __ldcg(g_QF + ((size_t)tb * 32 + hg * 8 + wg * 2) * 128 + (tid & 127));
  const uint4 qf1 = __ldcg(g_QF + ((size_t)tb * 32 + hg * 8 + wg * 2 + 1) * 128 + (tid & 127));
  mbar_wait(bars, 0);
  const uint32_t lutlane = LUT | (lane * 4);
  constexpr uint64_t KSTEP = 2048 >> 4, VSTEP = (16 * 16) >> 4;
  constexpr uint64_t KJUMP = (KVCH - 3 * 2048) >> 4, VJUMP = (KVCH - 4096) >> 4;
#pragma unroll 1
  for (int tile = 0; tile < 2; tile++) {
    const size_t fidx = ((size_t)tb * 32 + hg * 8 + wg * 2 + tile) * 128 + (tid & 127);
    const uint4 qv = tile ? qf1 : qf0;
    const uint32_t q[4] = {qv.x, qv.y, qv.z, qv.w};
    float o[12];
#pragma unroll
    for (int i = 0; i < 12; i++) o[i] = 0.f;
    {
      float s[32];
      uint32_t p[16];
      uint64_t kd = mkdesc(KS, 1024, 128, 0), vd = mkdesc(KS + 8192, 128, 4096, 0);
      fence_regs<12>(o);
      wg_fence();
      wgmma_rs_n64(s, q[0], q[1], q[2], q[3], kd, 0); kd += KSTEP;
      wg_commit();
#pragma unroll 1
      for (int c = 0; c < 8; c++) {
        if (c < 7) mbar_wait(bars + (c + 1) * 8, 0);
#pragma unroll
        for (int j = 0; j < 2; j++) {
          ATT_BLOCK(LUT_MASK_EVEN, j ? KJUMP : KSTEP)
          ATT_BLOCK(LUT_MASK_ODD, KSTEP)
        }
        vd += VJUMP;
      }
      wg_wait<0>(); fence_regs<12>(o); fence_regs<32>(s);
    }
    uint32_t unsafe;
    {
      const float4* kr = reinterpret_cast<const float4*>(sm0 + kred);
      float4 m = kr[lane];
#pragma unroll
      for (int i = 1; i < 4; i++) {
        const float4 v = kr[lane + 32 * i];
        m.x = fmaxf(m.x, v.x); m.y = fmaxf(m.y, v.y); m.z = fmaxf(m.z, v.z); m.w = fmaxf(m.w, v.w);
      }
#pragma unroll
      for (int of = 4; of < 32; of <<= 1) {
        m.x = fmaxf(m.x, __shfl_xor_sync(~0u, m.x, of)); m.y = fmaxf(m.y, __shfl_xor_sync(~0u, m.y, of));
        m.z = fmaxf(m.z, __shfl_xor_sync(~0u, m.z, of)); m.w = fmaxf(m.w, __shfl_xor_sync(~0u, m.w, of));
      }
      const float ax = __shfl_sync(~0u, m.x, t >> 1), ay = __shfl_sync(~0u, m.y, t >> 1), az = __shfl_sync(~0u, m.z, t >> 1), aw = __shfl_sync(~0u, m.w, t >> 1);
      const float bx = __shfl_sync(~0u, m.x, 2 + (t >> 1)), by = __shfl_sync(~0u, m.y, 2 + (t >> 1)), bz = __shfl_sync(~0u, m.z, 2 + (t >> 1)),
                  bw = __shfl_sync(~0u, m.w, 2 + (t >> 1));
      const float k0 = (t & 1) ? az : ax, k1 = (t & 1) ? aw : ay, k2 = (t & 1) ? bz : bx, k3 = (t & 1) ? bw : by;
      float b0 = fabsf(bf_lo(q[0])) * k0 + fabsf(bf_hi(q[0])) * k1 + fabsf(bf_lo(q[2])) * k2 + fabsf(bf_hi(q[2])) * k3;
      float b1 = fabsf(bf_lo(q[1])) * k0 + fabsf(bf_hi(q[1])) * k1 + fabsf(bf_lo(q[3])) * k2 + fabsf(bf_hi(q[3])) * k3;
      b0 += __shfl_xor_sync(~0u, b0, 1); b0 += __shfl_xor_sync(~0u, b0, 2);
      b1 += __shfl_xor_sync(~0u, b1, 1); b1 += __shfl_xor_sync(~0u, b1, 2);
      unsafe = __any_sync(~0u, !(b0 <= SAFE_SCORE_BOUND && b1 <= SAFE_SCORE_BOUND)) ? 1u : 0u;
    }
    if (unsafe) {
#pragma unroll
      for (int i = 0; i < 12; i++) o[i] = 0.f;
      float m0 = -INFINITY, m1 = -INFINITY;
#pragma unroll 1
      for (int kb = 0; kb < S_ / 16; kb++) {
        uint32_t kf[4];
        float sa[4] = {0.f, 0.f, 0.f, 0.f}, sc[4] = {0.f, 0.f, 0.f, 0.f};
        ldsm4(kf, KS + (kb >> 4) * KVCH + ((kb >> 2) & 3) * 2048 + ((lane >> 3) & 1) * 1024 + ((kb & 3) * 16 + (lane >> 4) * 8 + (lane & 7)) * 16);
        mma16816(sa, q, kf[0], kf[1]);
        mma16816(sc, q, kf[2], kf[3]);
        m0 = fmaxf(fmaxf(m0, fmaxf(sa[0], sa[1])), fmaxf(sc[0], sc[1]));
        m1 = fmaxf(fmaxf(m1, fmaxf(sa[2], sa[3])), fmaxf(sc[2], sc[3]));
      }
      m0 = fmaxf(m0, __shfl_xor_sync(~0u, m0, 1)); m0 = fmaxf(m0, __shfl_xor_sync(~0u, m0, 2));
      m1 = fmaxf(m1, __shfl_xor_sync(~0u, m1, 1)); m1 = fmaxf(m1, __shfl_xor_sync(~0u, m1, 2));
#pragma unroll 1
      for (int kb = 0; kb < S_ / 16; kb++) {
        uint32_t kf[4], vf[4], ef[4], a[4];
        float sa[4] = {0.f, 0.f, 0.f, 0.f}, sc[4] = {0.f, 0.f, 0.f, 0.f};
        const uint32_t chb = KS + (kb >> 4) * KVCH;
        ldsm4(kf, chb + ((kb >> 2) & 3) * 2048 + ((lane >> 3) & 1) * 1024 + ((kb & 3) * 16 + (lane >> 4) * 8 + (lane & 7)) * 16);
        const uint32_t krow = chb + 8192 + ((kb & 15) * 16 + (lane & 15)) * 16;
        ldsm4t(vf, krow + (lane >> 4) * 4096);
        ldsm4t(ef, krow + 8192);
        mma16816(sa, q, kf[0], kf[1]);
        mma16816(sc, q, kf[2], kf[3]);
        const uint32_t mask = ((kb >> 2) & 1) ? LUT_MASK_ODD : LUT_MASK_EVEN;
        const uint32_t sg0 = ((mask >> ((2 * kb) & 7)) & 1) ? 0x80008000u : 0u, sg1 = ((mask >> ((2 * kb + 1) & 7)) & 1) ? 0x80008000u : 0u;
        a[0] = pack_bf16(ex2f(sa[0] - m0), ex2f(sa[1] - m0)) ^ sg0;
        a[1] = pack_bf16(ex2f(sa[2] - m1), ex2f(sa[3] - m1)) ^ sg0;
        a[2] = pack_bf16(ex2f(sc[0] - m0), ex2f(sc[1] - m0)) ^ sg1;
        a[3] = pack_bf16(ex2f(sc[2] - m1), ex2f(sc[3] - m1)) ^ sg1;
        mma16816(o, a, vf[0], vf[1]);
        mma16816(o + 4, a, vf[2], vf[3]);
        mma16816(o + 8, a, ef[0], ef[1]);
      }
    }
    const float r0 = 1.f / o[8], r1 = 1.f / o[10];
    g_OF[fidx] = make_uint4(pack_bf16(o[0] * r0, o[1] * r0), pack_bf16(o[2] * r1, o[3] * r1), pack_bf16(o[4] * r0, o[5] * r0), pack_bf16(o[6] * r1, o[7] * r1));
  }
}

constexpr int ML_AUX = 180224;
constexpr int ML_PAR = ML_AUX + 49152;
constexpr int ML_SMEM = ML_PAR + 512 + 1920;
#define O0_PRE 3
#define F1_PRE 2
#define NB_2 3

#define RS_MAINLOOP(NCH, NB, GA, WAIT, MMA, FREE)                                                           \
  {                                                                                                         \
    uint4 afr[NB][4];                                                                                       \
    _Pragma("unroll") for (int c_ = 0; c_ < NB; c_++)                                                       \
      _Pragma("unroll") for (int ks = 0; ks < 4; ks++) afr[c_][ks] = __ldcg((GA) + (c_ * 4 + ks) * 128);    \
    _Pragma("unroll") for (int kc = 0; kc < NCH; kc++) {                                                    \
      WAIT;                                                                                                 \
      uint4* ac = afr[kc % NB];                                                                             \
      fence_regs_u<16>(reinterpret_cast<uint32_t*>(ac));                                                    \
      wg_fence();                                                                                           \
      _Pragma("unroll") for (int ks = 0; ks < 4; ks++) { const uint4 a = ac[ks]; MMA; }                     \
      wg_commit();                                                                                          \
      if (kc >= 1) {                                                                                        \
        wg_wait<1>();         \
        { const int kf = kc - 1; (void)kf; FREE; }                                                          \
        if (kc - 1 + NB < NCH) {                                                                            \
          uint4* an = afr[(kc - 1) % NB];                                                                   \
          fence_regs_u<16>(reinterpret_cast<uint32_t*>(an));                                                \
          _Pragma("unroll") for (int ks = 0; ks < 4; ks++) an[ks] = __ldcg((GA) + ((kc - 1 + NB) * 4 + ks) * 128); \
        }                                                                                                   \
      }                                                                                                     \
    }                                                                                                       \
    wg_wait<0>();                                                                                           \
  }

#define SM_MAINLOOP(NCH, SA, WAIT, MMA, FREE)                                                               \
  {                                                                                                         \
    uint4 afr[2][4];                                                                                        \
    _Pragma("unroll") for (int kc = 0; kc < NCH; kc++) {                                                    \
      WAIT;                                                                                                 \
      uint4* ac = afr[kc & 1];                                                                              \
      _Pragma("unroll") for (int ks = 0; ks < 4; ks++)                                                      \
        asm volatile("ld.shared.v4.u32 {%0,%1,%2,%3}, [%4];"                                                \
                     : "=r"(ac[ks].x), "=r"(ac[ks].y), "=r"(ac[ks].z), "=r"(ac[ks].w) : "r"((SA) + ks * 2048 + t1 * 16) : "memory"); \
      wg_fence();                                                                                           \
      _Pragma("unroll") for (int ks = 0; ks < 4; ks++) { const uint4 a = ac[ks]; MMA; }                     \
      wg_commit();                                                                                          \
      if (kc >= 1) {                                                                                        \
        wg_wait<1>();                \
        { const int kf = kc - 1; (void)kf; FREE; }                                                          \
      }                                                                                                     \
    }                                                                                                       \
    wg_wait<0>();                                                                                           \
  }

template <int NK>
__device__ __forceinline__ void residual_frags(const float* acc, const uint4* res, uint4* out, float2* __restrict__ stat, int w4, int lane) {
  float s0 = 0.f, q0 = 0.f, s1 = 0.f, q1 = 0.f;
#pragma unroll
  for (int k = 0; k < NK; k++) {
    const float* c = acc + 8 * k;
    const uint4 r = res[k];
    uint4 u;
    u.x = pack_bf16(bf_lo(r.x) + c[0], bf_hi(r.x) + c[1]);
    u.y = pack_bf16(bf_lo(r.y) + c[2], bf_hi(r.y) + c[3]);
    u.z = pack_bf16(bf_lo(r.z) + c[4], bf_hi(r.z) + c[5]);
    u.w = pack_bf16(bf_lo(r.w) + c[6], bf_hi(r.w) + c[7]);
    out[k] = u;
    s0 += (bf_lo(u.x) + bf_hi(u.x)) + (bf_lo(u.z) + bf_hi(u.z));
    q0 += bf_lo(u.x) * bf_lo(u.x) + bf_hi(u.x) * bf_hi(u.x) + bf_lo(u.z) * bf_lo(u.z) + bf_hi(u.z) * bf_hi(u.z);
    s1 += (bf_lo(u.y) + bf_hi(u.y)) + (bf_lo(u.w) + bf_hi(u.w));
    q1 += bf_lo(u.y) * bf_lo(u.y) + bf_hi(u.y) * bf_hi(u.y) + bf_lo(u.w) * bf_lo(u.w) + bf_hi(u.w) * bf_hi(u.w);
    if ((k & 3) == 3) {
#pragma unroll
      for (int o = 1; o < 4; o <<= 1) {
        s0 += __shfl_xor_sync(~0u, s0, o); q0 += __shfl_xor_sync(~0u, q0, o);
        s1 += __shfl_xor_sync(~0u, s1, o); q1 += __shfl_xor_sync(~0u, q1, o);
      }
      if ((lane & 3) == 0) {
        float2* st = stat + (k >> 2) * S_ + w4 * 16 + (lane >> 2);
        st[0] = make_float2(s0, q0);
        st[8] = make_float2(s1, q1);
      }
      s0 = q0 = s1 = q1 = 0.f;
    }
  }
}

__global__ void __cluster_dims__(2, 1, 1) __launch_bounds__(384, 1)
mlp_kernel(const __grid_constant__ CUtensorMap mWo, const __grid_constant__ CUtensorMap mW2, const __grid_constant__ CUtensorMap mWq,
           const __grid_constant__ CUtensorMap mOut, const bf16* __restrict__ wk, const bf16* __restrict__ wv, const bool LAST) {
  extern __shared__ __align__(1024) uint8_t smraw[];
  const uint32_t sb = smem_u32(smraw);
  uint8_t* sp = smraw;
  const uint32_t aux = sb + ML_AUX, bars = sb + ML_PAR;
  const uint32_t F0F = bars;
  const uint32_t B0 = bars + 64;
  const uint32_t F1F = bars + 72;
  const uint32_t E1 = bars + 104;
  const uint32_t L1 = bars + 136;
  const uint32_t F2F = bars + 184;
  const uint32_t E2 = bars + 272;
  const uint32_t L2 = bars + 296;
  const uint32_t F3F = bars + 304;
  const uint32_t B_RECV = bars + 368;
  auto a_slot = [&](int kc, uint32_t in_aux) { return kc < 6 ? sb + 131072 + kc * 8192 : in_aux + (kc - 6) * 8192; };
  float* s_par = reinterpret_cast<float*>(sp + ML_PAR + 512);
  const int tid = threadIdx.x, lane = tid & 31, warp = tid >> 5;
  const int b = blockIdx.x, mb = b >> 3;
  const int fs = b & 7;
  const int nt = (b & 7) >> 1, kh = b & 1;
  const int tb = b >> 2, hg = b & 3;
  pdl_trigger();
  if (tid == 0) {
    if (sb & 1023) __trap();
    tmap_prefetch(&mWo);
    tmap_prefetch(&mW2);
    if (LAST) tmap_prefetch(&mOut); else tmap_prefetch(&mWq);
    for (int i = 0; i < 8; i++) { mbar_init(F0F + i * 8, 1); mbar_init(F3F + i * 8, 1); }
    mbar_init(B0, 4);
    for (int i = 0; i < 4; i++) { mbar_init(F1F + i * 8, 1); mbar_init(E1 + i * 8, 8); mbar_init(L1 + i * 8, 8); }
    for (int i = 0; i < 11; i++) mbar_init(F2F + i * 8, 1);
    for (int i = 0; i < 3; i++) mbar_init(E2 + i * 8, 8);
    mbar_init(L2, 8);
    for (int w = 0; w < 2; w++) { mbar_init(B_RECV + w * 8, 1); mbar_expect(B_RECV + w * 8, 16384); }
    mbar_fence_init();
  }
  __syncthreads();
  asm volatile("barrier.cluster.arrive.relaxed.aligned;" ::: "memory");

  if (warp >= 8) {
  asm volatile("setmaxnreg.dec.sync.aligned.u32 56;");
  if (warp == 8) {
    if (lane == 0) {
#pragma unroll 1
      for (int kc = 0; kc < O0_PRE; kc++) {
        mbar_expect(F0F + kc * 8, 24576);
        tma3d(sb + kc * 16384, &mWo, 0, kc * 64, hg * 2, F0F + kc * 8);
      }
      pdl_wait();
#pragma unroll 1
      for (int kc = 0; kc < 8; kc++) {
        if (kc >= O0_PRE) mbar_expect(F0F + kc * 8, 24576);
        bulk_g2s(a_slot(kc, aux + 32768), g_OF + ((size_t)tb * 32 + kc * 4) * 128, 8192, F0F + kc * 8);
        if (kc >= O0_PRE) tma3d(sb + kc * 16384, &mWo, 0, kc * 64, hg * 2, F0F + kc * 8);
      }
      {
        const uint4* gA = g_x1F + (size_t)mb * 2 * 32 * 128;
        const uint8_t* gB = g_W1p + (size_t)fs * 8 * 28672;
        mbar_wait(B0, 0);
#pragma unroll 1
        for (int kc = 0; kc < 4; kc++) {
          mbar_expect(F1F + kc * 8, 45056);
          if (kc < F1_PRE) bulk_g2s(sb + kc * 45056 + 16384, gB + kc * 28672, 28672, F1F + kc * 8);
        }
        flag_wait(F_X1 + mb, 8);
#pragma unroll 1
        for (int kc = 0; kc < 8; kc++) {
          const uint32_t fb = F1F + (kc & 3) * 8, st = sb + (kc & 3) * 45056;
          if (kc >= 4) { mbar_wait(E1 + (kc & 3) * 8, 0); mbar_expect(fb, 45056); }
          bulk_g2s(st, gA + kc * 4 * 128, 8192, fb);
          bulk_g2s(st + 8192, gA + (32 + kc * 4) * 128, 8192, fb);
          if (kc >= F1_PRE) bulk_g2s(st + 16384, gB + kc * 28672, 28672, fb);
        }
      }
#pragma unroll 1
      for (int kc = 0; kc < 14; kc++) {
        const int s = kc < 11 ? kc : kc - 11;
        if (kc >= 11) mbar_wait(E2 + s * 8, 0);
        else mbar_wait(L1 + ((s * 16384 + 16383) / 45056) * 8, 0);
        mbar_expect(F2F + s * 8, 16384);
        tma3d(sb + s * 16384, &mW2, 0, kh * 896 + kc * 64, nt * 2, F2F + s * 8);
      }
      if (!LAST) {
        mbar_wait(L2, 0);
#pragma unroll 1
        for (int kc = 0; kc < 8; kc++) {
          mbar_expect(F3F + kc * 8, 24576);
          tma3d(sb + kc * 16384, &mWq, 0, kc * 64, hg * 2, F3F + kc * 8);
        }
        flag_wait(F_X2 + (tb >> 1), 16);
#pragma unroll 1
        for (int kc = 0; kc < 8; kc++) bulk_g2s(a_slot(kc, aux), g_x2F + ((size_t)tb * 32 + kc * 4) * 128, 8192, F3F + kc * 8);
      }
    }
  } else if (warp == 9) {
    pdl_wait();
#pragma unroll
    for (int i = 0; i < 7; i++) s_par[256 + i * 32 + lane] = __ldcg(g_cs1 + fs * 224 + i * 32 + lane);
    if (lane == 0) flag_wait(F_X1 + mb, 8);
    __syncwarp();
#pragma unroll
    for (int i = 0; i < 4; i++) {
      float mean, rstd;
      row_stats(g_statB, mb * 128 + i * 32 + lane, mean, rstd);
      s_par[i * 32 + lane] = mean; s_par[128 + i * 32 + lane] = rstd;
    }
    asm volatile("bar.arrive 1, 288;" ::: "memory");
    if (!LAST) {
      const bf16* wkv = (hg < 2 ? wk : wv) + (hg & 1) * 8;
#pragma unroll
      for (int i = 0; i < 16; i++)
        *reinterpret_cast<uint4*>(sp + ML_AUX + 32768 + (i * 32 + lane) * 16) = __ldg(reinterpret_cast<const uint4*>(wkv + (size_t)(i * 32 + lane) * 16));
      fence_async_smem();
      asm volatile("bar.arrive 7, 160;" ::: "memory");
      bar_sync(6, 288);
#pragma unroll
      for (int i = 0; i < 4; i++) s_par[128 + i * 32 + lane] = __ldcg(g_csQKV + hg * 136 + i * 32 + lane);
      if (lane < 8) s_par[256 + lane] = __ldcg(g_csQKV + hg * 136 + 128 + lane);
      if (lane == 0) flag_wait(F_X2 + (tb >> 1), 16);
      __syncwarp();
#pragma unroll
      for (int i = 0; i < 2; i++) {
        float mean, rstd;
        row_stats(g_statA, tb * 64 + i * 32 + lane, mean, rstd);
        s_par[i * 32 + lane] = mean; s_par[64 + i * 32 + lane] = rstd;
      }
      asm volatile("bar.arrive 1, 288;" ::: "memory");
    }
  }
  } else {
  asm volatile("setmaxnreg.inc.sync.aligned.u32 224;");
  const int wg = warp >> 2, w4 = warp & 3, g = lane >> 2, t = lane & 3, t1 = tid & 127;
  pdl_wait();
  if (wg == 0) {
    float acc[64];
#pragma unroll
    for (int i = 0; i < 64; i++) acc[i] = 0.f;
    fence_regs<64>(acc);
    uint4 res[8];
    {
      const uint4* gr = (LAST ? g_x2F : g_x0F) + ((size_t)tb * 32 + hg * 8) * 128 + t1;
#pragma unroll
      for (int k = 0; k < 8; k++) res[k] = __ldcg(gr + k * 128);
    }
    SM_MAINLOOP(8, a_slot(kc, aux + 32768), mbar_wait(F0F + kc * 8, 0),
                wgmma_rs_tb_n128(acc, a.x, a.y, a.z, a.w, mkdesc(sb + kc * 16384 + ks * 2048, 8192, 1024, 1), 1), )
    fence_regs<64>(acc);
    if (lane == 0) mbar_arrive(B0);
    uint4 out[8];
    residual_frags<8>(acc, res, out, g_statB + (hg * 2) * S_ + tb * 64, w4, lane);
    uint4* go = g_x1F + ((size_t)tb * 32 + hg * 8) * 128 + t1;
#pragma unroll
    for (int k = 0; k < 8; k++) go[k * 128] = out[k];
    bar_sync(2, 128);
    if (tid == 0) { flag_arrive(F_X1 + (tb >> 1)); }
  }
  {
    float acc[112];
#pragma unroll
    for (int i = 0; i < 112; i++) acc[i] = 0.f;
    fence_regs<112>(acc);
    SM_MAINLOOP(8, sb + (kc & 3) * 45056 + wg * 8192, mbar_wait(F1F + (kc & 3) * 8, kc >> 2),
                wgmma_rs_tb_n224(acc, a.x, a.y, a.z, a.w, mkdesc(sb + (kc & 3) * 45056 + 16384 + ks * 1024, 4096, 512, 2), 1),
                if (lane == 0) mbar_arrive((kf < 4 ? E1 : L1) + (kf & 3) * 8))
    fence_regs<112>(acc);
    if (lane == 0) mbar_arrive(L1 + 3 * 8);
    bar_sync(1, 288);
    const int rl0 = wg * 64 + w4 * 16 + g;
    const float mean0 = s_par[rl0], mean1 = s_par[rl0 + 8];
    const float kh0 = 0.5f * s_par[128 + rl0], kh1 = 0.5f * s_par[128 + rl0 + 8];
    const float* s_cs = s_par + 256;
    uint4* gh = g_hF + ((size_t)(mb * 2 + wg) * 112 + fs * 14) * 128 + t1;
#pragma unroll
    for (int j = 0; j < 28; j += 2) {
      uint32_t pk[4];
#pragma unroll
      for (int jj = 0; jj < 2; jj++) {
        const float2 c = *reinterpret_cast<const float2*>(s_cs + 8 * (j + jj) + 2 * t);
        const float* a = acc + 4 * (j + jj);
        float u[4] = {(a[0] - mean0 * c.x) * kh0, (a[1] - mean0 * c.y) * kh0, (a[2] - mean1 * c.x) * kh1, (a[3] - mean1 * c.y) * kh1};
#pragma unroll
        for (int i = 0; i < 4; i++) {
          float th;
          asm("tanh.approx.f32 %0, %1;" : "=f"(th) : "f"(u[i]));
          u[i] = fmaf(u[i], th, u[i]);
        }
        pk[jj * 2] = pack_bf16(u[0], u[1]);
        pk[jj * 2 + 1] = pack_bf16(u[2], u[3]);
      }
      gh[(j >> 1) * 128] = make_uint4(pk[0], pk[1], pk[2], pk[3]);
    }
    bar_sync(2 + wg, 128);
    if (!LAST) asm volatile("bar.arrive 6, 288;" ::: "memory");
    if (t1 == 0) flag_arrive(F_H + mb * 2 + (fs >> 2));
  }
  {
    float acc[64];
#pragma unroll
    for (int i = 0; i < 64; i++) acc[i] = 0.f;
    fence_regs<64>(acc);
    if (t1 == 0) flag_wait(F_H + mb * 2 + kh, 8);
    bar_sync(2 + wg, 128);
    uint4 res[4];
    {
      const uint4* gr = g_x1F + ((size_t)(mb * 2 + wg) * 32 + nt * 8 + kh * 4) * 128 + t1;
#pragma unroll
      for (int k = 0; k < 4; k++) res[k] = __ldcg(gr + k * 128);
    }
    const uint4* ga = g_hF + ((size_t)(mb * 2 + wg) * 112 + kh * 56) * 128 + t1;
    RS_MAINLOOP(14, NB_2, ga, mbar_wait(F2F + (kc < 11 ? kc : kc - 11) * 8, kc >= 11),
                wgmma_rs_tb_n128(acc, a.x, a.y, a.z, a.w, mkdesc(sb + (kc < 11 ? kc : kc - 11) * 16384 + ks * 2048, 8192, 1024, 1), 1),
                if (lane == 0 && kf < 3) mbar_arrive(E2 + kf * 8))
    fence_regs<64>(acc);
    if (lane == 0) mbar_arrive(L2);
    asm volatile("barrier.cluster.wait.acquire.aligned;" ::: "memory");
    {
      uint32_t dst, rbar;
      asm volatile("mapa.shared::cluster.u32 %0, %1, %2;" : "=r"(dst) : "r"(aux + wg * 16384 + t1 * 16), "r"(kh ^ 1));
      asm volatile("mapa.shared::cluster.u32 %0, %1, %2;" : "=r"(rbar) : "r"(B_RECV + wg * 8), "r"(kh ^ 1));
#pragma unroll
      for (int i = 0; i < 8; i++) {
        const float x0 = kh ? acc[4 * i] : acc[32 + 4 * i], x1 = kh ? acc[4 * i + 1] : acc[33 + 4 * i];
        const float x2 = kh ? acc[4 * i + 2] : acc[34 + 4 * i], x3 = kh ? acc[4 * i + 3] : acc[35 + 4 * i];
        asm volatile("st.async.weak.shared::cluster.mbarrier::complete_tx::bytes.v4.f32 [%0], {%1,%2,%3,%4}, [%5];"
                     ::"r"(dst + i * 2048), "f"(x0), "f"(x1), "f"(x2), "f"(x3), "r"(rbar) : "memory");
      }
    }
    mbar_wait_cluster(B_RECV + wg * 8, 0);
    float fin[32];
#pragma unroll
    for (int i = 0; i < 8; i++) {
      float4 v;
      asm volatile("ld.shared.v4.f32 {%0,%1,%2,%3}, [%4];" : "=f"(v.x), "=f"(v.y), "=f"(v.z), "=f"(v.w) : "r"(aux + wg * 16384 + t1 * 16 + i * 2048));
      fin[4 * i] = v.x + (kh ? acc[32 + 4 * i] : acc[4 * i]);
      fin[4 * i + 1] = v.y + (kh ? acc[33 + 4 * i] : acc[4 * i + 1]);
      fin[4 * i + 2] = v.z + (kh ? acc[34 + 4 * i] : acc[4 * i + 2]);
      fin[4 * i + 3] = v.w + (kh ? acc[35 + 4 * i] : acc[4 * i + 3]);
    }
    uint4 out[4];
    residual_frags<4>(fin, res, out, g_statA + (nt * 2 + kh) * S_ + mb * 128 + wg * 64, w4, lane);
    if (LAST) {
      const uint32_t stg = aux + 32768 + wg * 8192;
      const int rl = w4 * 16 + ((lane >> 3) & 1) * 8 + (lane & 7);
#pragma unroll
      for (int k = 0; k < 4; k++) stsm4(stg + rl * 128 + (((2 * k + (lane >> 4)) ^ (rl & 7)) << 4), out[k].x, out[k].y, out[k].z, out[k].w);
      fence_async_smem();
      bar_sync(2 + wg, 128);
      if (t1 == 0) {
        tma2d_store(&mOut, nt * 128 + kh * 64, mb * 128 + wg * 64, stg);
        bulk_commit_wait_all();
      }
    } else {
      uint4* go = g_x2F + ((size_t)(mb * 2 + wg) * 32 + nt * 8 + kh * 4) * 128 + t1;
#pragma unroll
      for (int k = 0; k < 4; k++) go[k * 128] = out[k];
      bar_sync(2 + wg, 128);
      if (t1 == 0) flag_arrive(F_X2 + mb);
    }
  }
  if (!LAST) {
    if (wg == 0) {
      float acc[64];
#pragma unroll
      for (int i = 0; i < 64; i++) acc[i] = 0.f;
      fence_regs<64>(acc);
      SM_MAINLOOP(8, a_slot(kc, aux), mbar_wait(F3F + kc * 8, 0),
                  wgmma_rs_tb_n128(acc, a.x, a.y, a.z, a.w, mkdesc(sb + kc * 16384 + ks * 2048, 8192, 1024, 1), 1), )
      fence_regs<64>(acc);
      bar_sync(1, 288);
      q_epilogue(acc, s_par, s_par + 64, s_par + 128, tb, hg, w4, lane);
    } else {
      float kv[4] = {0.f, 0.f, 0.f, 0.f};
      bar_sync(7, 160);
      fence_regs<4>(kv);
      SM_MAINLOOP(8, a_slot(kc, aux), mbar_wait(F3F + kc * 8, 0),
                  wgmma_rs_tb_n8(kv, a.x, a.y, a.z, a.w, mkdesc(aux + 32768 + kc * 1024 + ks * 256, 128, 128, 0), 1), )
      fence_regs<4>(kv);
      bar_sync(1, 288);
      const int rl0 = w4 * 16 + g, r0 = tb * 64 + rl0;
      kv_epilogue(kv, s_par[rl0], s_par[64 + rl0], s_par[rl0 + 8], s_par[64 + rl0 + 8], s_par[256 + 2 * t], s_par[256 + 2 * t + 1], s_par + 272, tb, hg,
                  r0, rl0, w4, lane, t1, 3);
    }
  }
  }
}

typedef CUresult (*EncodeFn)(CUtensorMap*, CUtensorMapDataType, cuuint32_t, void*, const cuuint64_t*, const cuuint64_t*, const cuuint32_t*,
                             const cuuint32_t*, CUtensorMapInterleave, CUtensorMapSwizzle, CUtensorMapL2promotion, CUtensorMapFloatOOBfill);

CUtensorMap make_map(EncodeFn fn, const void* base, int rank, const cuuint64_t* dims, const cuuint64_t* strides, const cuuint32_t* box,
                     CUtensorMapSwizzle swz) {
  CUtensorMap m;
  cuuint32_t es[3] = {1, 1, 1};
  fn(&m, CU_TENSOR_MAP_DATA_TYPE_BFLOAT16, rank, const_cast<void*>(base), dims, strides, box, es, CU_TENSOR_MAP_INTERLEAVE_NONE, swz,
     CU_TENSOR_MAP_L2_PROMOTION_NONE, CU_TENSOR_MAP_FLOAT_OOB_FILL_NONE);
  return m;
}
CUtensorMap map2d(EncodeFn fn, const void* base, int rows, int cols, int box_rows) {
  cuuint64_t dims[2] = {(cuuint64_t)cols, (cuuint64_t)rows}, strides[1] = {(cuuint64_t)cols * 2};
  cuuint32_t box[2] = {64, (cuuint32_t)box_rows};
  return make_map(fn, base, 2, dims, strides, box, CU_TENSOR_MAP_SWIZZLE_128B);
}
CUtensorMap map3d(EncodeFn fn, const void* base, int rows, int cols, int inner, int box_rows, int box_blocks) {
  cuuint64_t dims[3] = {(cuuint64_t)inner, (cuuint64_t)rows, (cuuint64_t)(cols / inner)};
  cuuint64_t strides[2] = {(cuuint64_t)cols * 2, (cuuint64_t)inner * 2};
  cuuint32_t box[3] = {(cuuint32_t)inner, (cuuint32_t)box_rows, (cuuint32_t)box_blocks};
  return make_map(fn, base, 3, dims, strides, box, inner == 64 ? CU_TENSOR_MAP_SWIZZLE_128B : CU_TENSOR_MAP_SWIZZLE_64B);
}

template <typename... KArgs, typename... Args>
void launch(void (*kern)(KArgs...), int grid, int block, int smem, bool pdl, Args... args) {
  cudaLaunchConfig_t cfg = {};
  cfg.gridDim = dim3(grid);
  cfg.blockDim = dim3(block);
  cfg.dynamicSmemBytes = smem;
  cfg.stream = cudaStreamPerThread;
  cudaLaunchAttribute at[1];
  at[0].id = cudaLaunchAttributeProgrammaticStreamSerialization;
  at[0].val.programmaticStreamSerializationAllowed = 1;
  cfg.attrs = at;
  cfg.numAttrs = pdl ? 1 : 0;
  cudaLaunchKernelEx(&cfg, kern, args...);
}

}

extern "C" void kernel_launch(void* const* d_in, const int* in_sizes, int n_in, void* d_out, int out_size) {
  const bf16* x = (const bf16*)d_in[0];
  const bf16* wq = (const bf16*)d_in[1];
  const bf16* wk = (const bf16*)d_in[2];
  const bf16* wv = (const bf16*)d_in[3];
  const bf16* wo = (const bf16*)d_in[4];
  const bf16* w1 = (const bf16*)d_in[6];
  const bf16* w2 = (const bf16*)d_in[7];

  void* fp = nullptr;
  cudaDriverEntryPointQueryResult qr;
  cudaGetDriverEntryPoint("cuTensorMapEncodeTiled", &fp, cudaEnableDefault, &qr);
  EncodeFn fn = (EncodeFn)fp;
  const CUtensorMap mOut = map2d(fn, d_out, S_, D_, 64), mX = map2d(fn, x, S_, D_, 64);
  const CUtensorMap mWq = map3d(fn, wq, D_, D_, 64, 64, 2), mWo = map3d(fn, wo, D_, D_, 64, 64, 2);
  const CUtensorMap mW1 = map3d(fn, w1, D_, F_, 32, 64, 7), mW2 = map3d(fn, w2, F_, D_, 64, 64, 2);

  cudaFuncSetAttribute(qkv_kernel, cudaFuncAttributeMaxDynamicSharedMemorySize, QKV_SMEM);
  cudaFuncSetAttribute(attn_kernel, cudaFuncAttributeMaxDynamicSharedMemorySize, ATT_SMEM);
  cudaFuncSetAttribute(mlp_kernel, cudaFuncAttributeMaxDynamicSharedMemorySize, ML_SMEM);

  launch(qkv_kernel, 132, 384, QKV_SMEM, false, mX, mWq, wk, wv);
  for (int layer = 0; layer < 2; layer++) {
    launch(attn_kernel, layer == 0 ? 128 + (int)NPACK : 128, 512, ATT_SMEM, true, mW1, wo, w2);
    launch(mlp_kernel, 128, 384, ML_SMEM, true, mWo, mW2, mWq, mOut, wk, wv, layer == 1);
  }
}
```
